```python
import torch

def _softmax(x, axis=-1):
    return torch.softmax(x, dim=axis)
def _gelu(x):
    return torch.nn.functional.gelu(x, approximate="tanh")
def _silu(x):
    return torch.nn.functional.silu(x)
def _sigmoid(x):
    return torch.sigmoid(x)
def _layernorm(x, axis=-1, eps=1e-5):
    m = x.mean(dim=axis, keepdim=True)
    v = x.var(dim=axis, keepdim=True, unbiased=False)
    return (x - m) / torch.sqrt(v + eps)
def _scatter_add(tgt, idx, src, axis=0):
    return tgt.clone().index_add_(axis, idx, src)
def _segment_sum(src, seg, n):
    out = torch.zeros((n,) + src.shape[1:], dtype=src.dtype)
    return out.index_add_(0, seg, src)
def _pad(x, pw):
    flat = tuple(v for pair in reversed(pw) for v in pair)
    return torch.nn.functional.pad(x, flat)

kernel_name = 'recurrent_scan__gqa_block_cached__dense_activation_gelu__decode'

def setup_inputs():

    _w = (lambda a: (lambda t: t.to(torch.bfloat16) if t.is_floating_point() else t)(torch.as_tensor(a)))
    def _A_setup():
        B, Sq, D = 8, 1, 512
        Hq, Hkv, Sk, Dh = 32, 8, 4096, 128
        assert Hq % Hkv == 0, (Hq, Hkv)
        return {
            "x": _w((lambda *s: torch.randn(*s, dtype=torch.bfloat16) * 0.05)(B, Sq, D)),
            "k_cache": _w((lambda *s: torch.randn(*s, dtype=torch.bfloat16) * 3.2)(B, Hkv, Sk, Dh)),
            "v_cache": _w((lambda *s: torch.randn(*s, dtype=torch.bfloat16) * 3.2)(B, Hkv, Sk, Dh)),
            "wq": _w((lambda *s: torch.randn(*s, dtype=torch.bfloat16) * 3.2)(D, Hq * Dh) * (D ** -0.5)),
            "wo": _w((lambda *s: torch.randn(*s, dtype=torch.bfloat16) * 3.2)(Hq * Dh, D) * ((Hq * Dh) ** -0.5)),
        }
    _A_in = _A_setup()

    def _B_setup():
        B, S, D, F = 8, 1, 512, 1792
        return {
            "x": _w((lambda *s: torch.randn(*s, dtype=torch.bfloat16) * 0.05)(B, S, D)),
            "w1": _w((lambda *s: torch.randn(*s, dtype=torch.bfloat16) * 3.2)(D, F) * (D ** -0.5)),
            "b1": _w((lambda *s: torch.randn(*s, dtype=torch.bfloat16) * 3.2)(F) * 0.01),
            "w2": _w((lambda *s: torch.randn(*s, dtype=torch.bfloat16) * 0.4)(F, D) * (F ** -0.5)),
            "b2": _w((lambda *s: torch.randn(*s, dtype=torch.bfloat16) * 0.4)(D) * 0.01),
        }
    _B_in = _B_setup()

    return {
        "A_x": _A_in["x"],
        "A_k_cache": _A_in["k_cache"],
        "A_v_cache": _A_in["v_cache"],
        "A_wq": _A_in["wq"],
        "A_wo": _A_in["wo"],
        "B_x": _B_in["x"],
        "B_w1": _B_in["w1"],
        "B_b1": _B_in["b1"],
        "B_w2": _B_in["w2"],
        "B_b2": _B_in["b2"],
    }

def reference(A_x, A_k_cache, A_v_cache, A_wq, A_wo, B_x, B_w1, B_b1, B_w2, B_b2):
    def _A_ref(x, k_cache, v_cache, wq, wo):
        B, Sq, D = x.shape
        Hq, Dh = 32, 128
        Hkv = k_cache.shape[1]
        rep = Hq // Hkv
        q = (lambda x, *d: x.permute(*d))((x @ wq).reshape(B, Sq, Hq, Dh), 0, 2, 1, 3)
        k = (lambda x, n, axis: torch.repeat_interleave(x, n, dim=axis))(k_cache, rep, axis=1)
        v = (lambda x, n, axis: torch.repeat_interleave(x, n, dim=axis))(v_cache, rep, axis=1)
        scores = torch.einsum("bhqd,bhkd->bhqk", q, k) * (Dh ** -0.5)
        p = _softmax(scores, axis=-1)
        o = torch.einsum("bhqk,bhkd->bhqd", p, v)
        return (lambda x, *d: x.permute(*d))(o, 0, 2, 1, 3).reshape(B, Sq, Hq * Dh) @ wo

    def _B_ref(x, w1, b1, w2, b2):
        h = torch.einsum("bsd,df->bsf", x, w1) + b1
        h = _gelu(h)
        return torch.einsum("bsf,fd->bsd", h, w2) + b2

    x = A_x
    xn = _layernorm(x, axis=-1)
    s = _A_ref(xn, A_k_cache, A_v_cache, A_wq, A_wo)
    g = _silu(_B_ref(xn, B_w1, B_b1, B_w2, B_b2))
    return x + s * g
```

```cpp
#include <cuda_runtime.h>
#include <cuda_bf16.h>
#include <cuda.h>
#include <stdint.h>

namespace {

constexpr int kB = 8, kD = 512, kHKV = 8, kSK = 4096;
constexpr int kGrid = 64, kFfnCtas = 0;
constexpr int kWarps = 18, kThreads = kWarps * 32;
constexpr int kSlot = 32768;
constexpr int kNSlot = 6;
constexpr int kItems = 70;
#define W_HEAD 3
#define N_HEAD 6
#define W_MAIN 4
#define WO_U 64
#define LEAD 1
#define PACE_END 2
#define W_TAIL W_MAIN
#define N_TAIL 60
#define GO_N 60
constexpr int kWoN = 4 + WO_U;

constexpr int kPStride = 2048 + 32;
constexpr int SM_RING = 0;
constexpr int SM_XO = kNSlot * kSlot;
constexpr int SM_H = SM_XO + 8 * 1040;
constexpr int SM_P = SM_H + 8 * 464;
constexpr int SM_SCR = SM_P + 4 * kPStride;
constexpr int SM_Q = SM_SCR + 4 * 2176;
constexpr int SM_ML = SM_Q + 1024;
constexpr int SM_PROG = SM_ML + 128;
constexpr int SM_BAR = SM_PROG + 32;
constexpr int B_FULL = 0, B_EMPTY = 8 * kNSlot, B_W = 16 * kNSlot, B_GO = B_W + 16, B_X = B_GO + 8, B_Q = B_X + 8,
              B_H = B_Q + 8, B_O = B_H + 8, B_END = B_O + 8;
constexpr int SM_TM = SM_BAR + B_END;
constexpr int SM_END = SM_TM;
constexpr int SM_BYTES = SM_END + 1024;
static_assert(SM_BYTES <= 232448, "smem");
static_assert(W_HEAD >= 2 && W_HEAD <= 4, "preamble covers the weight items only");

constexpr float kLog2e = 1.4426950408889634f;
constexpr uint32_t kSpinLimit = 1u << 22;
constexpr long long kWaitCycles = 1ll << 32;

struct Maps { CUtensorMap m[6]; };

__device__ __align__(128) uint32_t g_part[2][8][kB][kHKV][64];

#define TM(i)
#define TMDUMP()
#define TMCAL()

__device__ __forceinline__ uint32_t smem_u32(const void* p) { return (uint32_t)__cvta_generic_to_shared(p); }
__device__ __forceinline__ void mbar_init(uint32_t bar, uint32_t cnt) {
    asm volatile("mbarrier.init.shared::cta.b64 [%0], %1;" ::"r"(bar), "r"(cnt) : "memory");
}
__device__ __forceinline__ void mbar_expect_tx(uint32_t bar, uint32_t bytes) {
    asm volatile("mbarrier.arrive.expect_tx.shared::cta.b64 _, [%0], %1;" ::"r"(bar), "r"(bytes) : "memory");
}
__device__ __forceinline__ void mbar_arrive(uint32_t bar) {
    asm volatile("mbarrier.arrive.shared::cta.b64 _, [%0];" ::"r"(bar) : "memory");
}
__device__ __forceinline__ void mbar_arrive_n(uint32_t bar, uint32_t n) {
    asm volatile("mbarrier.arrive.shared::cta.b64 _, [%0], %1;" ::"r"(bar), "r"(n) : "memory");
}
__device__ __forceinline__ bool mbar_try(uint32_t bar, uint32_t parity) {
    uint32_t ok;
    asm volatile("{\n.reg .pred p;\nmbarrier.try_wait.parity.acquire.cluster.shared::cta.b64 p, [%1], %2;\nselp.u32 %0, 1, 0, p;\n}"
                 : "=r"(ok) : "r"(bar), "r"(parity) : "memory");
    return ok != 0u;
}
__device__ __forceinline__ bool mbar_try_cta(uint32_t bar, uint32_t parity) {
    uint32_t ok;
    asm volatile("{\n.reg .pred p;\nmbarrier.try_wait.parity.shared::cta.b64 p, [%1], %2;\nselp.u32 %0, 1, 0, p;\n}"
                 : "=r"(ok) : "r"(bar), "r"(parity) : "memory");
    return ok != 0u;
}
__device__ __forceinline__ bool mbar_test(uint32_t bar, uint32_t parity) {
    uint32_t ok;
    asm volatile("{\n.reg .pred p;\nmbarrier.test_wait.parity.shared::cta.b64 p, [%1], %2;\nselp.u32 %0, 1, 0, p;\n}"
                 : "=r"(ok) : "r"(bar), "r"(parity) : "memory");
    return ok != 0u;
}
__device__ __forceinline__ void mbar_wait(uint32_t bar, uint32_t parity) {
    if (mbar_try_cta(bar, parity)) return;
    const long long t0 = clock64();
    while (!mbar_try_cta(bar, parity))
        if (clock64() - t0 > kWaitCycles) __trap();
}
__device__ __forceinline__ void mbar_wait_cl(uint32_t bar, uint32_t parity) {
    if (mbar_try(bar, parity)) return;
    const long long t0 = clock64();
    while (!mbar_try(bar, parity))
        if (clock64() - t0 > kWaitCycles) __trap();
}
__device__ __forceinline__ void tma4d(uint32_t dst, const CUtensorMap* m, int c0, int c1, int c2, int c3, uint32_t bar) {
    asm volatile("cp.async.bulk.tensor.4d.shared::cluster.global.mbarrier::complete_tx::bytes [%0], [%1, {%3, %4, %5, %6}], [%2];"
                 ::"r"(dst), "l"(m), "r"(bar), "r"(c0), "r"(c1), "r"(c2), "r"(c3) : "memory");
}
__device__ __forceinline__ void tma3d(uint32_t dst, const CUtensorMap* m, int c0, int c1, int c2, uint32_t bar) {
    asm volatile("cp.async.bulk.tensor.3d.shared::cluster.global.mbarrier::complete_tx::bytes [%0], [%1, {%3, %4, %5}], [%2];"
                 ::"r"(dst), "l"(m), "r"(bar), "r"(c0), "r"(c1), "r"(c2) : "memory");
}
__device__ __forceinline__ void bar_sync(int id, int n) { asm volatile("barrier.sync %0, %1;" ::"r"(id), "r"(n) : "memory"); }
__device__ __forceinline__ void cluster_arrive() { asm volatile("barrier.cluster.arrive.relaxed;" ::: "memory"); }
__device__ __forceinline__ void cluster_wait() { asm volatile("barrier.cluster.wait;" ::: "memory"); }
__device__ __forceinline__ uint32_t mapa(uint32_t a, uint32_t rank) {
    uint32_t d;
    asm("mapa.shared::cluster.u32 %0, %1, %2;" : "=r"(d) : "r"(a), "r"(rank));
    return d;
}
__device__ __forceinline__ void st_async(uint32_t a, uint32_t v, uint32_t bar) {
    asm volatile("st.async.shared::cluster.mbarrier::complete_tx::bytes.u32 [%0], %1, [%2];" ::"r"(a), "r"(v), "r"(bar) : "memory");
}
__device__ __forceinline__ void st_async4(uint32_t a, uint32_t x, uint32_t y, uint32_t z, uint32_t w, uint32_t bar) {
    asm volatile("st.async.shared::cluster.mbarrier::complete_tx::bytes.v4.u32 [%0], {%1,%2,%3,%4}, [%5];"
                 ::"r"(a), "r"(x), "r"(y), "r"(z), "r"(w), "r"(bar) : "memory");
}

__device__ __forceinline__ void ldsm4(uint32_t (&r)[4], uint32_t a) {
    asm volatile("ldmatrix.sync.aligned.m8n8.x4.shared.b16 {%0,%1,%2,%3}, [%4];"
                 : "=r"(r[0]), "=r"(r[1]), "=r"(r[2]), "=r"(r[3]) : "r"(a) : "memory");
}
__device__ __forceinline__ void ldsm4t(uint32_t (&r)[4], uint32_t a) {
    asm volatile("ldmatrix.sync.aligned.m8n8.x4.trans.shared.b16 {%0,%1,%2,%3}, [%4];"
                 : "=r"(r[0]), "=r"(r[1]), "=r"(r[2]), "=r"(r[3]) : "r"(a) : "memory");
}
__device__ __forceinline__ void mma16816(float (&c)[4], const uint32_t (&a)[4], uint32_t b0, uint32_t b1) {
    asm volatile("mma.sync.aligned.m16n8k16.row.col.f32.bf16.bf16.f32 {%0,%1,%2,%3}, {%4,%5,%6,%7}, {%8,%9}, {%0,%1,%2,%3};"
                 : "+f"(c[0]), "+f"(c[1]), "+f"(c[2]), "+f"(c[3])
                 : "r"(a[0]), "r"(a[1]), "r"(a[2]), "r"(a[3]), "r"(b0), "r"(b1));
}
__device__ __forceinline__ uint32_t movm(uint32_t a) {
    uint32_t d;
    asm volatile("movmatrix.sync.aligned.m8n8.trans.b16 %0, %1;" : "=r"(d) : "r"(a));
    return d;
}
__device__ __forceinline__ uint32_t pack_bf16(float lo, float hi) {
    uint32_t d;
    asm("cvt.rn.bf16x2.f32 %0, %1, %2;" : "=r"(d) : "f"(hi), "f"(lo));
    return d;
}
__device__ __forceinline__ float bf_lo(uint32_t u) { return __uint_as_float(u << 16); }
__device__ __forceinline__ float bf_hi(uint32_t u) { return __uint_as_float(u & 0xffff0000u); }
__device__ __forceinline__ float bfr(float v) { return __uint_as_float(pack_bf16(0.f, v)); }
__device__ __forceinline__ uint32_t max_bf16x2(uint32_t a, uint32_t b) {
    uint32_t d;
    asm("max.bf16x2 %0, %1, %2;" : "=r"(d) : "r"(a), "r"(b));
    return d;
}
__device__ __forceinline__ float ex2(float x) {
    float y;
    asm("ex2.approx.ftz.f32 %0, %1;" : "=f"(y) : "f"(x));
    return y;
}
__device__ __forceinline__ float mul_sigmoid(float v, float z) { return __fdividef(v, 1.0f + ex2(fminf(-kLog2e * z, 120.f))); }
__device__ __forceinline__ uint32_t lds32(uint32_t a) { uint32_t v; asm volatile("ld.shared.u32 %0, [%1];" : "=r"(v) : "r"(a) : "memory"); return v; }
__device__ __forceinline__ float2 ldsf2(uint32_t a) { float2 v; asm volatile("ld.shared.v2.f32 {%0,%1}, [%2];" : "=f"(v.x), "=f"(v.y) : "r"(a) : "memory"); return v; }
__device__ __forceinline__ uint4 lds128(uint32_t a) {
    uint4 v;
    asm volatile("ld.shared.v4.u32 {%0,%1,%2,%3}, [%4];" : "=r"(v.x), "=r"(v.y), "=r"(v.z), "=r"(v.w) : "r"(a) : "memory");
    return v;
}
__device__ __forceinline__ void sts32(uint32_t a, uint32_t v) { asm volatile("st.shared.u32 [%0], %1;" ::"r"(a), "r"(v) : "memory"); }
__device__ __forceinline__ void stsf(uint32_t a, float v) { asm volatile("st.shared.f32 [%0], %1;" ::"r"(a), "f"(v) : "memory"); }
__device__ __forceinline__ void sts128(uint32_t a, uint32_t x, uint32_t y, uint32_t z, uint32_t w) {
    asm volatile("st.shared.v4.u32 [%0], {%1,%2,%3,%4};" ::"r"(a), "r"(x), "r"(y), "r"(z), "r"(w) : "memory");
}
__device__ __forceinline__ uint32_t encf(float v) { const uint32_t b = __float_as_uint(v); return b == 0u ? 0x80000000u : b; }
__device__ __forceinline__ void st_rlx2_pred(uint32_t* p, uint32_t a, uint32_t b, bool c) {
    asm volatile("{\n.reg .pred p;\nsetp.ne.u32 p, %3, 0;\n@p st.relaxed.gpu.global.v2.u32 [%0], {%1,%2};\n}" ::"l"(p), "r"(a), "r"(b), "r"((uint32_t)c) : "memory");
}
__device__ __forceinline__ void st_pred32(void* p, uint32_t v, bool c) {
    asm volatile("{\n.reg .pred p;\nsetp.ne.u32 p, %2, 0;\n@p st.global.u32 [%0], %1;\n}" ::"l"(p), "r"(v), "r"((uint32_t)c) : "memory");
}
__device__ __forceinline__ void ld_rlx2_pred(uint2& v, const uint32_t* p, bool c) {
    asm volatile("{\n.reg .pred p;\nsetp.ne.u32 p, %3, 0;\n@p ld.relaxed.gpu.global.v2.u32 {%0,%1}, [%2];\n}"
                 : "+r"(v.x), "+r"(v.y) : "l"(p), "r"((uint32_t)c) : "memory");
}
__device__ __forceinline__ uint32_t ldg32(const void* p) {
    uint32_t v;
    asm volatile("ld.global.nc.u32 %0, [%1];" : "=r"(v) : "l"(p));
    return v;
}

__global__ void __cluster_dims__(8, 1, 1) __launch_bounds__(kThreads, 1)
fused_decode_kernel(const __nv_bfloat16* __restrict__ x, const __nv_bfloat16* __restrict__ b1,
                    const __nv_bfloat16* __restrict__ b2, __nv_bfloat16* __restrict__ out,
                    const __grid_constant__ Maps maps) {
    extern __shared__ __align__(1024) unsigned char smem_raw[];
    const uint32_t sb = (smem_u32(smem_raw) + 1023u) & ~1023u;
    const uint32_t bars = sb + SM_BAR;
    const int tid = threadIdx.x, wid = tid >> 5, lane = tid & 31;
    const int hkv = blockIdx.x >> 3, r = blockIdx.x & 7;

    TM(0);
    auto issue_w = [&](int n) {
        const uint32_t bar = bars + B_FULL + 8 * n, dst = sb + SM_RING + n * kSlot;
        if (n < 2) {
            mbar_expect_tx(bar, kSlot);
            tma3d(dst, &maps.m[2], blockIdx.x * 64, n * 256, 0, bar);
        } else if (n == 2) {
            mbar_expect_tx(bar, r < 7 ? kSlot : 0);
            if (r < 7) tma3d(dst, &maps.m[3], hkv * 224 + r * 32, 0, 0, bar);
        } else {
            mbar_expect_tx(bar, 224 * 128);
            tma3d(dst, &maps.m[4], r * 64, hkv * 224, 0, bar);
        }
    };
    if (wid == 1) asm volatile("prefetch.global.L1 [%0];" ::"l"(x + r * kD + lane * 16) : "memory");
    if (tid == 0) {
#pragma unroll
        for (int n = 0; n < kNSlot; n++) mbar_init(bars + B_FULL + 8 * n, 1);
        asm volatile("fence.mbarrier_init.release.cluster;" ::: "memory");
#pragma unroll
        for (int n = 0; n < W_HEAD; n++) issue_w(n);
    }
    if (tid == 64) {
#pragma unroll
        for (int n = 0; n < kNSlot; n++) mbar_init(bars + B_EMPTY + 8 * n, 8);
#pragma unroll
        for (int n = B_W; n < B_END; n += 8) mbar_init(bars + n, 1);
        asm volatile("fence.mbarrier_init.release.cluster;" ::: "memory");
        sts128(sb + SM_PROG, 0, 0, 0, 0);
        sts128(sb + SM_PROG + 16, 0, 0, 0, 0);
        asm volatile("fence.release.sync_restrict::shared::cta.cluster;" ::: "memory");
        mbar_expect_tx(bars + B_X, 8192);
        mbar_expect_tx(bars + B_Q, 1024);
        mbar_expect_tx(bars + B_H, 3584);
        mbar_expect_tx(bars + B_O, 8192);
    }
    __syncwarp();
    cluster_arrive();
    TM(11);
    const int w = (wid - 2) & 7;
    const int g = lane >> 2, t = lane & 3, r7 = lane & 7, mi = lane >> 3;

    if (wid == 1) {
        {
            const uint4* xr = reinterpret_cast<const uint4*>(x + r * kD) + lane;
            const uint4 xv0 = __ldg(xr), xv1 = __ldg(xr + 32);
            float f[16];
            const uint32_t u[8] = {xv0.x, xv0.y, xv0.z, xv0.w, xv1.x, xv1.y, xv1.z, xv1.w};
#pragma unroll
            for (int i = 0; i < 8; i++) { f[2 * i] = bf_lo(u[i]); f[2 * i + 1] = bf_hi(u[i]); }
            float s = 0.f;
#pragma unroll
            for (int i = 0; i < 16; i++) s += f[i];
#pragma unroll
            for (int o = 16; o; o >>= 1) s += __shfl_xor_sync(0xffffffffu, s, o);
            TM(13);
            const float mean = s * (1.0f / kD);
            float vs = 0.f;
#pragma unroll
            for (int i = 0; i < 16; i++) { const float d = f[i] - mean; vs = fmaf(d, d, vs); }
#pragma unroll
            for (int o = 16; o; o >>= 1) vs += __shfl_xor_sync(0xffffffffu, vs, o);
            const float mb = bfr(mean);
            const float den = bfr(__fsqrt_rn(bfr(bfr(vs * (1.0f / kD)) + 1e-5f)));
            const float rden = __frcp_rn(den);
            uint32_t q[8];
#pragma unroll
            for (int i = 0; i < 8; i++) {
                const uint32_t d2 = pack_bf16(f[2 * i] - mb, f[2 * i + 1] - mb);
                q[i] = pack_bf16(bf_lo(d2) * rden, bf_hi(d2) * rden);
            }
            cluster_wait();
#pragma unroll 1
            for (int d = 0; d < 8; d++) {
                const uint32_t rb = mapa(sb, d), xa = rb + SM_XO + r * 1040 + lane * 16;
                st_async4(xa, q[0], q[1], q[2], q[3], rb + SM_BAR + B_X);
                st_async4(xa + 512, q[4], q[5], q[6], q[7], rb + SM_BAR + B_X);
            }
            TM(12);
        }
        const int col = r * 64 + 2 * lane;
        const uint32_t xw = ldg32(x + hkv * kD + col), bw = ldg32(b2 + col);
        mbar_wait(bars + B_GO, 0);
        float g0 = 0.f, g1 = 0.f;
#pragma unroll 1
        for (int pass = 0; pass < 2; pass++) {
            uint32_t* src = &g_part[pass][r][hkv][0][2 * lane];
            uint2 sv[8];
#pragma unroll
            for (int c = 0; c < 8; c++) sv[c] = make_uint2(0u, 0u);
            for (uint32_t it = 0;; it++) {
#pragma unroll
                for (int c = 0; c < 8; c++) ld_rlx2_pred(sv[c], src + c * 64, sv[c].x == 0u || sv[c].y == 0u);
                const uint32_t m = min(min(min(min(sv[0].x, sv[0].y), min(sv[1].x, sv[1].y)), min(min(sv[2].x, sv[2].y), min(sv[3].x, sv[3].y))),
                                       min(min(min(sv[4].x, sv[4].y), min(sv[5].x, sv[5].y)), min(min(sv[6].x, sv[6].y), min(sv[7].x, sv[7].y))));
                if (m != 0u) break;
                if (it > kSpinLimit) __trap();
                if (!mbar_test(bars + B_O, 0)) __nanosleep(200);
            }
            float s0 = 0.f, s1 = 0.f;
            {
                float a[8], b[8];
#pragma unroll
                for (int c = 0; c < 8; c++) { a[c] = __uint_as_float(sv[c].x); b[c] = __uint_as_float(sv[c].y); }
                s0 = ((a[0] + a[1]) + (a[2] + a[3])) + ((a[4] + a[5]) + (a[6] + a[7]));
                s1 = ((b[0] + b[1]) + (b[2] + b[3])) + ((b[4] + b[5]) + (b[6] + b[7]));
            }
            const uint32_t sw = pack_bf16(s0, s1);
            const uint32_t pw = pack_bf16(bf_lo(sw) * g0, bf_hi(sw) * g1);
            st_pred32(out + hkv * kD + col, pack_bf16(bf_lo(xw) + bf_lo(pw), bf_hi(xw) + bf_hi(pw)), pass);
#pragma unroll
            for (int c = 0; c < 8; c++) *reinterpret_cast<uint2*>(src + c * 64) = make_uint2(0u, 0u);
            const uint32_t yw = pack_bf16(bf_lo(sw) + bf_lo(bw), bf_hi(sw) + bf_hi(bw));
            g0 = bfr(mul_sigmoid(bf_lo(yw), bf_lo(yw)));
            g1 = bfr(mul_sigmoid(bf_hi(yw), bf_hi(yw)));
        }
        TM(10);
    } else if (wid == 0) {
        cluster_wait();
        const int kvrow0 = (r * kHKV + hkv) * kSK;
        const uint32_t prog_remote = mapa(sb + SM_PROG + r * 4, lane & 7);
        int slot = W_HEAD, ph = 0;
        int landed = 0, lslot = 0, lph = 0;
#pragma unroll 1
        for (int n = W_HEAD; n < kItems; n++) {
            if (n >= kNSlot) mbar_wait(bars + B_EMPTY + 8 * slot, ph ^ 1);
            const int need = n - (n < N_HEAD ? W_HEAD : (n < N_TAIL ? W_MAIN : W_TAIL)) + 1;
            while (landed < need) {
                if (landed > n - kNSlot) mbar_wait(bars + B_FULL + 8 * lslot, lph);
                landed++;
                if (++lslot == kNSlot) { lslot = 0; lph ^= 1; }
            }
            if (LEAD < kItems && n < kItems - PACE_END) {
                if (lane < 8) asm volatile("st.relaxed.cluster.shared::cluster.u32 [%0], %1;" ::"r"(prog_remote), "r"(n) : "memory");
                for (uint32_t it = 0;; it++) {
                    int p;
                    asm volatile("ld.relaxed.cluster.shared::cta.u32 %0, [%1];" : "=r"(p) : "r"(sb + SM_PROG + (lane & 7) * 4) : "memory");
                    if (__all_sync(0xffffffffu, max(p, W_HEAD) + LEAD >= n)) break;
                    if (it > kSpinLimit * 16) __trap();
                }
            }
            if (lane == 0) {
                const uint32_t fb = bars + B_FULL + 8 * slot, dst = sb + SM_RING + slot * kSlot;
                if (n < 4) {
                    if (W_HEAD <= 2 && n == 2) issue_w(2);
                    if (W_HEAD <= 3 && n == 3) issue_w(3);
                } else if ((unsigned)(n - kWoN) < 2u) {
                    const uint32_t wb = bars + B_W + 8 * (n - kWoN);
                    mbar_expect_tx(wb, kSlot);
                    tma4d(dst, &maps.m[5], r * 64, 0, 0, hkv * 32 + (n - kWoN) * 16, wb);
                    mbar_arrive(fb);
                } else {
                    const int u = n - (n < kWoN ? 4 : 6);
                    mbar_expect_tx(fb, kSlot);
                    tma3d(dst, &maps.m[(u >> 3) & 1], 0, kvrow0 + (u >> 4) * 1024 + (u & 7) * 128, 0, fb);
                }
                if (n == GO_N) mbar_arrive(bars + B_GO);
            }
            __syncwarp();
            if (++slot == kNSlot) { slot = 0; ph ^= 1; }
        }
        TM(1);
    } else if (wid < 10) {
        const int kg = w >> 1, ch = w & 1;
        const uint32_t b1w = ldg32(b1 + hkv * 224 + (r < 7 ? r : 0) * 32 + 2 * (lane & 15));
        const uint32_t aoff = (r7 + 8 * (mi >> 1)) * 128 + (((4 * ch + (mi & 1)) ^ r7) << 4);
        cluster_wait();
#pragma unroll 1
        for (int pass = 0; pass < 4; pass++) {
            int slot, arow, nks;
            uint32_t abar, bbar, baddr, astep = 2048, ao = aoff;
            if (pass == 1) {
                slot = 2; arow = w * 32; nks = 4; bbar = B_X;
                baddr = SM_XO + r7 * 1040 + w * 128;
                astep = 1024;
                ao = (r7 + 8 * (mi >> 1)) * 64 + (((mi & 1) ^ (r7 >> 1)) << 4);
            } else if (pass == 2) {
                const int k0 = kg < 3 ? kg * 4 : 11;
                slot = 3; arow = k0 * 16; nks = kg < 2 ? 4 : 3; bbar = B_H;
                baddr = SM_H + r7 * 464 + k0 * 32;
            } else {
                slot = pass == 0 ? (kg >> 1) : ((kg >> 1) ? (kWoN + 1) % kNSlot : kWoN % kNSlot);
                arow = (kg & 1) * 128; nks = 8; bbar = pass == 0 ? B_X : B_O;
                baddr = SM_XO + r7 * 1040 + kg * 256;
            }
            abar = pass == 3 ? B_W + 8 * (kg >> 1) : B_FULL + 8 * slot;
            baddr += sb + mi * 16;
            const uint32_t abase = sb + SM_RING + slot * kSlot + arow * 128 + ao;
            uint32_t af[8][2][4];
            mbar_wait(bars + abar, 0);
#pragma unroll
            for (int ks = 0; ks < 8; ks++) {
                if (ks < 4 || nks == 8) {
                    ldsm4t(af[ks][0], abase + ks * (ks < 4 ? astep : 2048));
                    ldsm4t(af[ks][1], (abase ^ 32) + ks * (ks < 4 ? astep : 2048));
                }
            }
            __syncwarp();
            if (lane == 0) mbar_arrive_n(bars + B_EMPTY + 8 * slot, nks == 8 ? 2 : 1);
            if (pass == 0) TM(2);
            TM(14);
            mbar_wait_cl(bars + bbar, 0);
            TM(8);
            float acc[2][2][4];
#pragma unroll
            for (int i = 0; i < 16; i++) acc[i >> 3][(i >> 2) & 1][i & 3] = 0.f;
            uint32_t bf[4][4];
            ldsm4(bf[0], baddr);
            ldsm4(bf[1], baddr + 64);
            if (nks == 8) {
                ldsm4(bf[2], baddr + 128);
                ldsm4(bf[3], baddr + 192);
            }
#pragma unroll
            for (int ks = 0; ks < 8; ks++) {
                if (ks < 3 || ks < nks) {
                    mma16816(acc[0][ks & 1], af[ks][0], bf[ks >> 1][2 * (ks & 1)], bf[ks >> 1][2 * (ks & 1) + 1]);
                    mma16816(acc[1][ks & 1], af[ks][1], bf[ks >> 1][2 * (ks & 1)], bf[ks >> 1][2 * (ks & 1) + 1]);
                }
            }
#pragma unroll
            for (int mt = 0; mt < 2; mt++) {
#pragma unroll
                for (int e = 0; e < 4; e++)
                    stsf(sb + SM_SCR + kg * 2176 + (2 * t + (e & 1)) * 272 + (ch * 32 + mt * 16 + g + 8 * (e >> 1)) * 4,
                         acc[mt][0][e] + acc[mt][1][e]);
            }
            bar_sync(1, 256);
            const uint32_t ra = sb + SM_SCR + w * 272 + lane * 8;
            const float2 p0 = ldsf2(ra), p1 = ldsf2(ra + 2176), p2 = ldsf2(ra + 2 * 2176), p3 = ldsf2(ra + 3 * 2176);
            float s0 = (p0.x + p1.x) + (p2.x + p3.x), s1 = (p0.y + p1.y) + (p2.y + p3.y);
            st_rlx2_pred(&g_part[pass & 1][r][w][hkv][2 * lane], encf(s0), encf(s1), pass >= 2);
            TM(9);
            if (pass == 0) {
                const uint32_t rb = mapa(sb, w);
                st_async(rb + SM_Q + (r * 32 + lane) * 4, pack_bf16(s0, s1), rb + SM_BAR + B_Q);
                TM(3);
            } else if (pass == 1) {
                s0 += __shfl_xor_sync(0xffffffffu, s0, 16);
                s1 += __shfl_xor_sync(0xffffffffu, s1, 16);
                const uint32_t sw = pack_bf16(s0, s1);
                const uint32_t vw = pack_bf16(bf_lo(sw) + bf_lo(b1w), bf_hi(sw) + bf_hi(b1w));
                const float v0 = bf_lo(vw), v1 = bf_hi(vw);
                const float c = 2.0f * 0.7978845608028654f;
                const uint32_t hw = pack_bf16(mul_sigmoid(v0, c * (v0 + 0.044715f * v0 * v0 * v0)),
                                              mul_sigmoid(v1, c * (v1 + 0.044715f * v1 * v1 * v1)));
                if (r < 7) {
#pragma unroll
                    for (int d = 0; d < 4; d++) {
                        const uint32_t rb = mapa(sb, (lane >> 4) * 4 + d);
                        st_async(rb + SM_H + w * 464 + r * 64 + (lane & 15) * 4, hw, rb + SM_BAR + B_H);
                    }
                }
            } else if (pass == 2) {
                TM(15);
            }
            if (pass < 3) bar_sync(1, 256);
        }
    } else {
        TMCAL();
        int slot = 4, ph = 0, u = 0;
        auto acquire = [&]() {
            if (u++ == WO_U) {
                slot += 2;
                if (slot >= kNSlot) { slot -= kNSlot; ph ^= 1; }
            }
            mbar_wait(bars + B_FULL + 8 * slot, ph);
            return sb + SM_RING + slot * kSlot;
        };
        auto release = [&]() {
            __syncwarp();
            if (lane == 0) mbar_arrive(bars + B_EMPTY + 8 * slot);
            if (++slot == kNSlot) { slot = 0; ph ^= 1; }
        };
        uint32_t koff[4];
#pragma unroll
        for (int c = 0; c < 4; c++)
            koff[c] = (w * 16 + r7 + 8 * (mi & 1)) * 128 + (((2 * c + (lane >> 4)) ^ r7) << 4);
        const uint32_t voff = (w >> 2) * 16384 + (r7 + 8 * (lane >> 4)) * 128 + (((2 * (w & 3) + (mi & 1)) ^ r7) << 4);
        const int ht = 2 * (t & 1) + (t >> 1);
        cluster_wait();
        uint32_t qf[8][2];
        mbar_wait_cl(bars + B_Q, 0);
#pragma unroll
        for (int ks = 0; ks < 8; ks++) {
            qf[ks][0] = lds32(sb + SM_Q + ((g & 3) * 64 + ks * 8 + t) * 4);
            qf[ks][1] = lds32(sb + SM_Q + ((g & 3) * 64 + ks * 8 + 4 + t) * 4);
        }
        TM(4);
        uint32_t mx2 = 0xff80ff80u;
        uint32_t mprev = 0xff80ff80u;
        float Mw = -INFINITY, l = 0.f, fin = 0.f;
        float O[4][4];
#pragma unroll
        for (int i = 0; i < 4; i++) { O[i][0] = O[i][1] = O[i][2] = O[i][3] = 0.f; }
#pragma unroll 1
        for (int c = 0; c < 4; c++) {
            uint32_t pa = sb + SM_P + (g & 3) * kPStride + (lane >> 4) * 16 + t * 4 + w * 32;
#pragma unroll 1
            for (int it = 0; it < 8; it++) {
                const uint32_t base = acquire();
                float sa[4] = {0.f, 0.f, 0.f, 0.f}, sb2[4] = {0.f, 0.f, 0.f, 0.f};
                uint32_t kf[8][4];
#pragma unroll
                for (int ks = 0; ks < 8; ks++) ldsm4(kf[ks], base + (ks >> 2) * 16384 + koff[ks & 3]);
#pragma unroll
                for (int ks = 0; ks < 8; ks += 2) {
                    mma16816(sa, kf[ks], qf[ks][0], qf[ks][1]);
                    mma16816(sb2, kf[ks + 1], qf[ks + 1][0], qf[ks + 1][1]);
                }
                release();
                const float c0 = t < 2 ? sa[0] + sb2[0] : sa[2] + sb2[2];
                const float c1 = t < 2 ? sa[1] + sb2[1] : sa[3] + sb2[3];
                const float scale = 0.08838834764831845f;
                const uint32_t s2 = pack_bf16(c0, c1);
                const uint32_t v = pack_bf16(bf_lo(s2) * scale, bf_hi(s2) * scale);
                mx2 = max_bf16x2(mx2, v);
                sts32(pa, movm(v));
                pa += 256;
            }
            {
#pragma unroll
                for (int o = 2; o <= 16; o <<= 1) mx2 = max_bf16x2(mx2, __shfl_xor_sync(0xffffffffu, mx2, o));
                if (lane < 2) sts32(sb + SM_ML + lane * 32 + w * 4, mx2);
                bar_sync(2, 256);
                const uint4 a0 = lds128(sb + SM_ML), a1 = lds128(sb + SM_ML + 16);
                const uint4 b0 = lds128(sb + SM_ML + 32), b1v = lds128(sb + SM_ML + 48);
                const uint32_t m01 = max_bf16x2(max_bf16x2(max_bf16x2(a0.x, a0.y), max_bf16x2(a0.z, a0.w)),
                                                max_bf16x2(max_bf16x2(a1.x, a1.y), max_bf16x2(a1.z, a1.w)));
                const uint32_t m23 = max_bf16x2(max_bf16x2(max_bf16x2(b0.x, b0.y), max_bf16x2(b0.z, b0.w)),
                                                max_bf16x2(max_bf16x2(b1v.x, b1v.y), max_bf16x2(b1v.z, b1v.w)));
                const uint32_t mw = (w & 4) ? m23 : m01, mt = (t & 1) ? m23 : m01;
                const float M = (w & 2) ? bf_hi(mw) : bf_lo(mw);
                l *= ex2((Mw - M) * kLog2e);
                Mw = M;
                const float al0 = ex2((bf_lo(mprev) - bf_lo(mt)) * kLog2e), al1 = ex2((bf_hi(mprev) - bf_hi(mt)) * kLog2e);
                mprev = mt;
#pragma unroll
                for (int i = 0; i < 4; i++) { O[i][0] *= al0; O[i][1] *= al1; O[i][2] *= al0; O[i][3] *= al1; }
                const uint32_t ea = sb + SM_P + (w >> 1) * kPStride + (w & 1) * 1024 + lane * 16;
#pragma unroll
                for (int i = 0; i < 2; i++) {
                    const uint4 sv = lds128(ea + i * 512);
                    const uint32_t uu[4] = {sv.x, sv.y, sv.z, sv.w};
                    uint32_t rr[4];
#pragma unroll
                    for (int e = 0; e < 4; e++) {
                        const float p0 = ex2((bf_lo(uu[e]) - M) * kLog2e), p1 = ex2((bf_hi(uu[e]) - M) * kLog2e);
                        l += p0 + p1;
                        rr[e] = pack_bf16(p0, p1);
                    }
                    sts128(ea + i * 512, rr[0], rr[1], rr[2], rr[3]);
                }
                float ls = l;
#pragma unroll
                for (int o = 16; o; o >>= 1) ls += __shfl_xor_sync(0xffffffffu, ls, o);
                if (lane == 0) stsf(sb + SM_ML + 64 + w * 4, ls);
                bar_sync(2, 256);
                const float2 lp = ldsf2(sb + SM_ML + 64 + ht * 8);
                fin = __fdividef(1.0f, lp.x + lp.y);
                TM(5);
            }
            pa = sb + SM_P + (r7 & 3) * kPStride + mi * 16;
#pragma unroll 1
            for (int it = 0; it < 8; it++) {
                uint32_t pf[4][4];
#pragma unroll
                for (int i = 0; i < 4; i++) ldsm4(pf[i], pa + i * 64);
                pa += 256;
                const uint32_t base = acquire() + voff;
                uint32_t vf[8][4];
#pragma unroll
                for (int i = 0; i < 8; i++) ldsm4t(vf[i], base + i * 2048);
#pragma unroll
                for (int i = 0; i < 8; i++) mma16816(O[i & 3], vf[i], pf[i >> 1][2 * (i & 1)], pf[i >> 1][2 * (i & 1) + 1]);
                release();
            }
            if (c == 0) mbar_wait_cl(bars + B_H, 0);
        }
        TM(6);
        const float lo = t < 2 ? (O[0][0] + O[1][0]) + (O[2][0] + O[3][0]) : (O[0][1] + O[1][1]) + (O[2][1] + O[3][1]);
        const float hi = t < 2 ? (O[0][2] + O[1][2]) + (O[2][2] + O[3][2]) : (O[0][3] + O[1][3]) + (O[2][3] + O[3][3]);
        const uint32_t ow = pack_bf16(lo * fin, hi * fin);
        const uint32_t oa = SM_XO + r * 1040 + (ht * 64 + w * 8 + g) * 4;
#pragma unroll
        for (int d = 0; d < 8; d++) {
            const uint32_t rb = mapa(sb, d);
            st_async(rb + oa, ow, rb + SM_BAR + B_O);
        }
        TM(7);
    }
    TMDUMP();
}

typedef CUresult (*EncodeFn)(CUtensorMap*, CUtensorMapDataType, cuuint32_t, void*, const cuuint64_t*, const cuuint64_t*,
                             const cuuint32_t*, const cuuint32_t*, CUtensorMapInterleave, CUtensorMapSwizzle,
                             CUtensorMapL2promotion, CUtensorMapFloatOOBfill);

void encode(EncodeFn fn, CUtensorMap* m, void* p, int rank, const cuuint64_t* dims, const cuuint64_t* strides,
            const cuuint32_t* box, CUtensorMapSwizzle sw = CU_TENSOR_MAP_SWIZZLE_128B) {
    const cuuint32_t es[4] = {1, 1, 1, 1};
    fn(m, CU_TENSOR_MAP_DATA_TYPE_BFLOAT16, rank, p, dims, strides, box, es, CU_TENSOR_MAP_INTERLEAVE_NONE,
       sw, CU_TENSOR_MAP_L2_PROMOTION_L2_256B, CU_TENSOR_MAP_FLOAT_OOB_FILL_NONE);
}

}

extern "C" void kernel_launch(void* const* d_in, const int* in_sizes, int n_in, void* d_out, int out_size) {
    (void)in_sizes; (void)n_in; (void)out_size;
    void* fnp = nullptr;
    cudaDriverEntryPointQueryResult qr;
    cudaGetDriverEntryPoint("cuTensorMapEncodeTiled", &fnp, cudaEnableDefault, &qr);
    EncodeFn fn = (EncodeFn)fnp;
    Maps maps;
    {
        const cuuint64_t dims[3] = {64, (cuuint64_t)kB * kHKV * kSK, 2}, str[2] = {256, 128};
        const cuuint32_t box[3] = {64, 128, 2};
        encode(fn, &maps.m[0], d_in[1], 3, dims, str, box);
        encode(fn, &maps.m[1], d_in[2], 3, dims, str, box);
    }
    {
        const cuuint64_t dims[3] = {4096, 512, 1}, str[2] = {8192, 8192 * 512};
        const cuuint32_t box[3] = {64, 256, 1};
        encode(fn, &maps.m[2], d_in[3], 3, dims, str, box);
    }
    {
        const cuuint64_t dims[3] = {1792, 256, 2}, str[2] = {3584, 3584 * 256};
        const cuuint32_t box[3] = {32, 256, 2};
        encode(fn, &maps.m[3], d_in[6], 3, dims, str, box, CU_TENSOR_MAP_SWIZZLE_64B);
    }
    {
        const cuuint64_t dims[3] = {512, 1792, 1}, str[2] = {1024, 1024 * 1792};
        const cuuint32_t box[3] = {64, 224, 1};
        encode(fn, &maps.m[4], d_in[8], 3, dims, str, box);
    }
    {
        const cuuint64_t dims[4] = {512, 2, 8, 256}, str[3] = {8 * 1024, 1024, 16 * 1024};
        const cuuint32_t box[4] = {64, 2, 8, 16};
        encode(fn, &maps.m[5], d_in[4], 4, dims, str, box);
    }
    cudaFuncSetAttribute(fused_decode_kernel, cudaFuncAttributeMaxDynamicSharedMemorySize, SM_BYTES);
    fused_decode_kernel<<<kGrid, kThreads, SM_BYTES>>>(
        (const __nv_bfloat16*)d_in[0], (const __nv_bfloat16*)d_in[7], (const __nv_bfloat16*)d_in[9],
        (__nv_bfloat16*)d_out, maps);
}
```

```cpp
#include <cuda_runtime.h>
#include <cuda_bf16.h>
#include <cuda.h>
#include <stdint.h>

namespace {

constexpr int kB = 8, kD = 512, kHKV = 8, kSK = 4096;
constexpr int kGrid = 64, kFfnCtas = 0;
constexpr int kWarps = 18, kThreads = kWarps * 32;
constexpr int kSlot = 32768;
constexpr int kNSlot = 6;
constexpr int kItems = 70;
#define W_HEAD 3
#define N_HEAD 6
#define W_MAIN 4
#define WO_U 64
#define LEAD 1
#define PACE_END 2
#define W_TAIL W_MAIN
#define N_TAIL 60
#define EARLY_PF 0
#define HEAD_T0 2200
#define HEAD_DT 1100
#define PR_KV 3
#define PR_WQ 3
#define PR_W1 3
#define PR_W2 3
#define PR_WO 3
#define ROT 0
#define ROT_M 1
#define SCHED_B 660
#define SCHED_A (SCHED_E - 69 * SCHED_B)
#define SCHED_D 300
#define SCHED_E 43500
#define GO_N 40
constexpr int kWoN = 4 + WO_U;

constexpr int kPStride = 2048 + 32;
constexpr int SM_RING = 0;
constexpr int SM_H = kNSlot * kSlot;
constexpr int SM_XO = SM_H + 8 * 512;
constexpr int SM_P = SM_XO + 8 * 1024;
constexpr int SM_SCR = SM_P + 4 * kPStride;
constexpr int SM_Q = SM_SCR + 4 * 2176;
constexpr int SM_G = SM_Q + 1024;
constexpr int SM_ML = SM_G + 2048;
constexpr int SM_B1 = SM_ML + 128;
constexpr int SM_PROG = SM_B1 + 64;
constexpr int SM_BAR = SM_PROG + 32;
constexpr int B_FULL = 0, B_EMPTY = 8 * kNSlot, B_W = 16 * kNSlot, B_GO = B_W + 16, B_X = B_GO + 8, B_Q = B_X + 8,
              B_H = B_Q + 8, B_O = B_H + 8, B_END = B_O + 8;
constexpr int SM_TM = SM_BAR + B_END;
constexpr int SM_END = SM_TM;
constexpr int SM_BYTES = SM_END + 1024;
static_assert(SM_BYTES <= 232448, "smem");
static_assert(W_HEAD >= 2 && W_HEAD <= 4, "preamble covers the weight items only");

constexpr float kLog2e = 1.4426950408889634f;
constexpr uint32_t kSpinLimit = 1u << 22;
constexpr long long kWaitCycles = 1ll << 32;

struct Maps { CUtensorMap m[6]; };

__device__ __align__(128) uint32_t g_part[2][8][kB][kHKV][64];

#define TM(i)
#define TMDUMP()
#define TMCAL()

__device__ __forceinline__ uint32_t smem_u32(const void* p) { return (uint32_t)__cvta_generic_to_shared(p); }
__device__ __forceinline__ void mbar_init(uint32_t bar, uint32_t cnt) {
    asm volatile("mbarrier.init.shared::cta.b64 [%0], %1;" ::"r"(bar), "r"(cnt) : "memory");
}
__device__ __forceinline__ void mbar_expect_tx(uint32_t bar, uint32_t bytes) {
    asm volatile("mbarrier.arrive.expect_tx.shared::cta.b64 _, [%0], %1;" ::"r"(bar), "r"(bytes) : "memory");
}
__device__ __forceinline__ void mbar_arrive(uint32_t bar) {
    asm volatile("mbarrier.arrive.shared::cta.b64 _, [%0];" ::"r"(bar) : "memory");
}
__device__ __forceinline__ void mbar_arrive_n(uint32_t bar, uint32_t n) {
    asm volatile("mbarrier.arrive.shared::cta.b64 _, [%0], %1;" ::"r"(bar), "r"(n) : "memory");
}
__device__ __forceinline__ bool mbar_try(uint32_t bar, uint32_t parity) {
    uint32_t ok;
    asm volatile("{\n.reg .pred p;\nmbarrier.try_wait.parity.relaxed.cluster.shared::cta.b64 p, [%1], %2;\nselp.u32 %0, 1, 0, p;\n}"
                 : "=r"(ok) : "r"(bar), "r"(parity) : "memory");
    return ok != 0u;
}
__device__ __forceinline__ bool mbar_try_cta(uint32_t bar, uint32_t parity) {
    uint32_t ok;
    asm volatile("{\n.reg .pred p;\nmbarrier.try_wait.parity.shared::cta.b64 p, [%1], %2;\nselp.u32 %0, 1, 0, p;\n}"
                 : "=r"(ok) : "r"(bar), "r"(parity) : "memory");
    return ok != 0u;
}
__device__ __forceinline__ bool mbar_test(uint32_t bar, uint32_t parity) {
    uint32_t ok;
    asm volatile("{\n.reg .pred p;\nmbarrier.test_wait.parity.shared::cta.b64 p, [%1], %2;\nselp.u32 %0, 1, 0, p;\n}"
                 : "=r"(ok) : "r"(bar), "r"(parity) : "memory");
    return ok != 0u;
}
__device__ __forceinline__ void mbar_wait(uint32_t bar, uint32_t parity) {
    if (mbar_try_cta(bar, parity)) return;
    const long long t0 = clock64();
    while (!mbar_try_cta(bar, parity))
        if (clock64() - t0 > kWaitCycles) __trap();
}
__device__ __forceinline__ void mbar_wait_cl(uint32_t bar, uint32_t parity) {
    if (!mbar_try(bar, parity)) {
        const long long t0 = clock64();
        while (!mbar_try(bar, parity))
            if (clock64() - t0 > kWaitCycles) __trap();
    }
    asm volatile("fence.acquire.sync_restrict::shared::cluster.cluster;" ::: "memory");
}
#define PIN(x) asm volatile("shfl.sync.bfly.b32 %0, %0, 0, 0x1f, 0xffffffff;" : "+r"(x) :: "memory")
#define PINF(x) asm volatile("" : "+f"(x) :: "memory")
#define PINL(x) asm volatile("{\n.reg .b32 lo, hi;\nmov.b64 {lo, hi}, %0;\nshfl.sync.bfly.b32 lo, lo, 0, 0x1f, 0xffffffff;\n" \
                             "shfl.sync.bfly.b32 hi, hi, 0, 0x1f, 0xffffffff;\nmov.b64 %0, {lo, hi};\n}" : "+l"(x) :: "memory")
#define EVF 1
constexpr uint64_t kEvictFirst = 0x12F0000000000000ull;
__device__ __forceinline__ void tma4d(uint32_t dst, const CUtensorMap* m, int c0, int c1, int c2, int c3, uint32_t bar) {
    asm volatile("cp.async.bulk.tensor.4d.shared::cluster.global.mbarrier::complete_tx::bytes [%0], [%1, {%3, %4, %5, %6}], [%2];"
                 ::"r"(dst), "l"(m), "r"(bar), "r"(c0), "r"(c1), "r"(c2), "r"(c3) : "memory");
}
template <bool kHint>
__device__ __forceinline__ void tma3d(uint32_t dst, const CUtensorMap* m, int c0, int c1, int c2, uint32_t bar) {
    if (kHint)
        asm volatile("cp.async.bulk.tensor.3d.shared::cluster.global.mbarrier::complete_tx::bytes.L2::cache_hint [%0], [%1, {%3, %4, %5}], [%2], %6;"
                     ::"r"(dst), "l"(m), "r"(bar), "r"(c0), "r"(c1), "r"(c2), "l"(kEvictFirst) : "memory");
    else
        asm volatile("cp.async.bulk.tensor.3d.shared::cluster.global.mbarrier::complete_tx::bytes [%0], [%1, {%3, %4, %5}], [%2];"
                     ::"r"(dst), "l"(m), "r"(bar), "r"(c0), "r"(c1), "r"(c2) : "memory");
}
__device__ __forceinline__ void bar_sync(int id, int n) { asm volatile("barrier.sync %0, %1;" ::"r"(id), "r"(n) : "memory"); }
__device__ __forceinline__ void bar_arrive(int id, int n) { asm volatile("barrier.arrive %0, %1;" ::"r"(id), "r"(n) : "memory"); }
__device__ __forceinline__ void cluster_arrive() { asm volatile("barrier.cluster.arrive.relaxed;" ::: "memory"); }
__device__ __forceinline__ void cluster_wait() { asm volatile("barrier.cluster.wait;" ::: "memory"); }
__device__ __forceinline__ uint32_t mapa(uint32_t a, uint32_t rank) {
    uint32_t d;
    asm("mapa.shared::cluster.u32 %0, %1, %2;" : "=r"(d) : "r"(a), "r"(rank));
    return d;
}
__device__ __forceinline__ void st_async(uint32_t a, uint32_t v, uint32_t bar) {
    asm volatile("st.async.shared::cluster.mbarrier::complete_tx::bytes.u32 [%0], %1, [%2];" ::"r"(a), "r"(v), "r"(bar) : "memory");
}
__device__ __forceinline__ void st_async4(uint32_t a, uint32_t x, uint32_t y, uint32_t z, uint32_t w, uint32_t bar) {
    asm volatile("st.async.shared::cluster.mbarrier::complete_tx::bytes.v4.u32 [%0], {%1,%2,%3,%4}, [%5];"
                 ::"r"(a), "r"(x), "r"(y), "r"(z), "r"(w), "r"(bar) : "memory");
}

__device__ __forceinline__ void ldsm4(uint32_t (&r)[4], uint32_t a) {
    asm volatile("ldmatrix.sync.aligned.m8n8.x4.shared.b16 {%0,%1,%2,%3}, [%4];"
                 : "=r"(r[0]), "=r"(r[1]), "=r"(r[2]), "=r"(r[3]) : "r"(a) : "memory");
}
__device__ __forceinline__ void ldsm4t(uint32_t (&r)[4], uint32_t a) {
    asm volatile("ldmatrix.sync.aligned.m8n8.x4.trans.shared.b16 {%0,%1,%2,%3}, [%4];"
                 : "=r"(r[0]), "=r"(r[1]), "=r"(r[2]), "=r"(r[3]) : "r"(a) : "memory");
}
__device__ __forceinline__ void mma16816(float (&c)[4], const uint32_t (&a)[4], uint32_t b0, uint32_t b1) {
    asm volatile("mma.sync.aligned.m16n8k16.row.col.f32.bf16.bf16.f32 {%0,%1,%2,%3}, {%4,%5,%6,%7}, {%8,%9}, {%0,%1,%2,%3};"
                 : "+f"(c[0]), "+f"(c[1]), "+f"(c[2]), "+f"(c[3])
                 : "r"(a[0]), "r"(a[1]), "r"(a[2]), "r"(a[3]), "r"(b0), "r"(b1));
}
__device__ __forceinline__ uint32_t movm(uint32_t a) {
    uint32_t d;
    asm volatile("movmatrix.sync.aligned.m8n8.trans.b16 %0, %1;" : "=r"(d) : "r"(a));
    return d;
}
__device__ __forceinline__ uint32_t pack_bf16(float lo, float hi) {
    uint32_t d;
    asm("cvt.rn.bf16x2.f32 %0, %1, %2;" : "=r"(d) : "f"(hi), "f"(lo));
    return d;
}
__device__ __forceinline__ float bf_lo(uint32_t u) { return __uint_as_float(u << 16); }
__device__ __forceinline__ float bf_hi(uint32_t u) { return __uint_as_float(u & 0xffff0000u); }
__device__ __forceinline__ float bfr(float v) { return __uint_as_float(pack_bf16(0.f, v)); }
__device__ __forceinline__ uint32_t max_bf16x2(uint32_t a, uint32_t b) {
    uint32_t d;
    asm("max.bf16x2 %0, %1, %2;" : "=r"(d) : "r"(a), "r"(b));
    return d;
}
__device__ __forceinline__ float ex2(float x) {
    float y;
    asm("ex2.approx.ftz.f32 %0, %1;" : "=f"(y) : "f"(x));
    return y;
}
__device__ __forceinline__ float mul_sigmoid(float v, float z) { return __fdividef(v, 1.0f + ex2(fminf(-kLog2e * z, 120.f))); }
__device__ __forceinline__ uint32_t lds32(uint32_t a) { uint32_t v; asm volatile("ld.shared.u32 %0, [%1];" : "=r"(v) : "r"(a) : "memory"); return v; }
__device__ __forceinline__ float2 ldsf2(uint32_t a) { float2 v; asm volatile("ld.shared.v2.f32 {%0,%1}, [%2];" : "=f"(v.x), "=f"(v.y) : "r"(a) : "memory"); return v; }
__device__ __forceinline__ uint4 lds128(uint32_t a) {
    uint4 v;
    asm volatile("ld.shared.v4.u32 {%0,%1,%2,%3}, [%4];" : "=r"(v.x), "=r"(v.y), "=r"(v.z), "=r"(v.w) : "r"(a) : "memory");
    return v;
}
__device__ __forceinline__ void sts32(uint32_t a, uint32_t v) { asm volatile("st.shared.u32 [%0], %1;" ::"r"(a), "r"(v) : "memory"); }
__device__ __forceinline__ void stsf(uint32_t a, float v) { asm volatile("st.shared.f32 [%0], %1;" ::"r"(a), "f"(v) : "memory"); }
__device__ __forceinline__ void sts128(uint32_t a, uint32_t x, uint32_t y, uint32_t z, uint32_t w) {
    asm volatile("st.shared.v4.u32 [%0], {%1,%2,%3,%4};" ::"r"(a), "r"(x), "r"(y), "r"(z), "r"(w) : "memory");
}
__device__ __forceinline__ uint32_t encf(float v) { const uint32_t b = __float_as_uint(v); return b == 0u ? 0x80000000u : b; }
__device__ __forceinline__ void st_rlx2_pred(uint32_t* p, uint32_t a, uint32_t b, bool c) {
    asm volatile("{\n.reg .pred p;\nsetp.ne.u32 p, %3, 0;\n@p st.relaxed.gpu.global.v2.u32 [%0], {%1,%2};\n}" ::"l"(p), "r"(a), "r"(b), "r"((uint32_t)c) : "memory");
}
__device__ __forceinline__ void st_pred32(void* p, uint32_t v, bool c) {
    asm volatile("{\n.reg .pred p;\nsetp.ne.u32 p, %2, 0;\n@p st.global.u32 [%0], %1;\n}" ::"l"(p), "r"(v), "r"((uint32_t)c) : "memory");
}
__device__ __forceinline__ void ld_rlx2_pred(uint2& v, const uint32_t* p, bool c) {
    asm volatile("{\n.reg .pred p;\nsetp.ne.u32 p, %3, 0;\n@p ld.relaxed.gpu.global.v2.u32 {%0,%1}, [%2];\n}"
                 : "+r"(v.x), "+r"(v.y) : "l"(p), "r"((uint32_t)c) : "memory");
}
__device__ __forceinline__ uint2 ld_rlx2(const uint32_t* p) {
    uint2 v;
    asm volatile("ld.relaxed.gpu.global.v2.u32 {%0,%1}, [%2];" : "=r"(v.x), "=r"(v.y) : "l"(p) : "memory");
    return v;
}
__device__ __forceinline__ uint32_t clock32() { uint32_t c; asm volatile("mov.u32 %0, %clock;" : "=r"(c) :: "memory"); return c; }
__device__ __forceinline__ uint32_t gt32() { uint32_t c; asm volatile("mov.u32 %0, %globaltimer_lo;" : "=r"(c) :: "memory"); return c; }
__device__ __forceinline__ bool gather_try(const uint32_t* p, uint32_t dst) {
    const uint2 v = ld_rlx2(p);
    const bool ok = __all_sync(0xffffffffu, v.x != 0u && v.y != 0u);
    asm volatile("{\n.reg .pred p;\nsetp.ne.u32 p, %3, 0;\n@p st.shared.v2.u32 [%0], {%1,%2};\n}"
                 ::"r"(dst), "r"(v.x), "r"(v.y), "r"((uint32_t)ok) : "memory");
    return ok;
}
__device__ __forceinline__ uint32_t ldg32(const void* p) {
    uint32_t v;
    asm volatile("ld.global.nc.u32 %0, [%1];" : "=r"(v) : "l"(p));
    return v;
}

__global__ void __cluster_dims__(8, 1, 1) __launch_bounds__(kThreads, 1)
fused_decode_kernel(const __nv_bfloat16* __restrict__ x, const __nv_bfloat16* __restrict__ b1,
                    const __nv_bfloat16* __restrict__ b2, __nv_bfloat16* __restrict__ out,
                    const __nv_bfloat16* __restrict__ wq,
                    const __grid_constant__ Maps maps) {
    extern __shared__ __align__(1024) unsigned char smem_raw[];
    const uint32_t sb = (smem_u32(smem_raw) + 1023u) & ~1023u;
    const uint32_t bars = sb + SM_BAR;
    const int tid = threadIdx.x, wid = tid >> 5, lane = tid & 31;
    const int hkv = blockIdx.x >> 3, r = blockIdx.x & 7;

    TM(0);
    auto issue_w = [&](int n) {
        const uint32_t bar = bars + B_FULL + 8 * n, dst = sb + SM_RING + n * kSlot;
        if (n < 2) {
            mbar_expect_tx(bar, kSlot);
            tma3d<(EVF & 2) != 0>(dst, &maps.m[2], blockIdx.x * 64, n * 256, 0, bar);
        } else if (n == 2) {
            mbar_expect_tx(bar, r < 7 ? kSlot : 0);
            if (r < 7) tma3d<(EVF & 2) != 0>(dst, &maps.m[3], hkv * 224 + r * 32, 0, 0, bar);
        } else {
            mbar_expect_tx(bar, 224 * 128);
            tma3d<(EVF & 2) != 0>(dst, &maps.m[4], r * 64, hkv * 224, 0, bar);
        }
    };
    if (wid == 1) asm volatile("prefetch.global.L1 [%0];" ::"l"(x + r * kD + lane * 16) : "memory");
    const uint32_t t_start = SCHED_B ? gt32() : clock32();
    if (tid == 0) {
#pragma unroll
        for (int n = 0; n < kNSlot; n++) mbar_init(bars + B_FULL + 8 * n, 1);
        asm volatile("fence.mbarrier_init.release.cluster;" ::: "memory");
#pragma unroll
        for (int n = 0; n < W_HEAD; n++) {
            issue_w(n);
        }
    }
    if (tid == 64) {
#pragma unroll
        for (int n = 0; n < kNSlot; n++) mbar_init(bars + B_EMPTY + 8 * n, 8);
#pragma unroll
        for (int n = B_W; n < B_END; n += 8) mbar_init(bars + n, 1);
        asm volatile("fence.mbarrier_init.release.cluster;" ::: "memory");
        sts128(sb + SM_PROG, 0, 0, 0, 0);
        sts128(sb + SM_PROG + 16, 0, 0, 0, 0);
        asm volatile("fence.release.sync_restrict::shared::cta.cluster;" ::: "memory");
        mbar_expect_tx(bars + B_X, 8192);
        mbar_expect_tx(bars + B_Q, 1024);
        mbar_expect_tx(bars + B_H, 3584);
        mbar_expect_tx(bars + B_O, 8192);
    }
    __syncwarp();
    cluster_arrive();
    TM(11);
    const int w = (wid - 2) & 7;
    const int g = lane >> 2, t = lane & 3, r7 = lane & 7, mi = lane >> 3;

    if (wid == 1) {
        {
            const uint4* xr = reinterpret_cast<const uint4*>(x + r * kD) + lane;
            const uint4 xv0 = __ldg(xr), xv1 = __ldg(xr + 32);
            float f[16];
            const uint32_t u[8] = {xv0.x, xv0.y, xv0.z, xv0.w, xv1.x, xv1.y, xv1.z, xv1.w};
#pragma unroll
            for (int i = 0; i < 8; i++) { f[2 * i] = bf_lo(u[i]); f[2 * i + 1] = bf_hi(u[i]); }
            float s = 0.f;
#pragma unroll
            for (int i = 0; i < 16; i++) s += f[i];
#pragma unroll
            for (int o = 16; o; o >>= 1) s += __shfl_xor_sync(0xffffffffu, s, o);
            TM(13);
            const float mean = s * (1.0f / kD);
            float vs = 0.f;
#pragma unroll
            for (int i = 0; i < 16; i++) { const float d = f[i] - mean; vs = fmaf(d, d, vs); }
#pragma unroll
            for (int o = 16; o; o >>= 1) vs += __shfl_xor_sync(0xffffffffu, vs, o);
            const float mb = bfr(mean);
            const float den = bfr(__fsqrt_rn(bfr(bfr(vs * (1.0f / kD)) + 1e-5f)));
            const float rden = __frcp_rn(den);
            uint32_t q[8];
#pragma unroll
            for (int i = 0; i < 8; i++) {
                const uint32_t d2 = pack_bf16(f[2 * i] - mb, f[2 * i + 1] - mb);
                q[i] = pack_bf16(bf_lo(d2) * rden, bf_hi(d2) * rden);
            }
            const uint32_t xoff = SM_XO + r * 1024 + ((lane >> 1) & 7) * 128 + (((2 * (lane >> 4) + (lane & 1)) ^ r) << 4);
            cluster_wait();
#pragma unroll 1
            for (int d = 0; d < 8; d++) {
                const uint32_t rb = mapa(sb, d), xa = rb + xoff;
                st_async4(xa, q[0], q[1], q[2], q[3], rb + SM_BAR + B_X);
                st_async4(xa ^ 64, q[4], q[5], q[6], q[7], rb + SM_BAR + B_X);
            }
            TM(12);
        }
        const int col = r * 64 + 2 * lane;
        const uint32_t xw = ldg32(x + hkv * kD + col), bw = ldg32(b2 + col);
        float g0 = 0.f, g1 = 0.f;
#pragma unroll 1
        for (int pass = 0; pass < 2; pass++) {
            bar_sync(3, 288);
            float2 sv[8];
#pragma unroll
            for (int c = 0; c < 8; c++) sv[c] = ldsf2(sb + SM_G + c * 256 + lane * 8);
            const float s0 = ((sv[0].x + sv[1].x) + (sv[2].x + sv[3].x)) + ((sv[4].x + sv[5].x) + (sv[6].x + sv[7].x));
            const float s1 = ((sv[0].y + sv[1].y) + (sv[2].y + sv[3].y)) + ((sv[4].y + sv[5].y) + (sv[6].y + sv[7].y));
            const uint32_t sw = pack_bf16(s0, s1);
            const uint32_t pw = pack_bf16(bf_lo(sw) * g0, bf_hi(sw) * g1);
            st_pred32(out + hkv * kD + col, pack_bf16(bf_lo(xw) + bf_lo(pw), bf_hi(xw) + bf_hi(pw)), pass);
            TM(10);
            if (pass == 0) bar_arrive(4, 288);
            const uint32_t yw = pack_bf16(bf_lo(sw) + bf_lo(bw), bf_hi(sw) + bf_hi(bw));
            g0 = bfr(mul_sigmoid(bf_lo(yw), bf_lo(yw)));
            g1 = bfr(mul_sigmoid(bf_hi(yw), bf_hi(yw)));
        }
    } else if (wid == 0) {
        cluster_wait();
        const int kvrow0 = (r * kHKV + hkv) * kSK;
        const int rot = ROT;
        const uint32_t prog_remote = mapa(sb + SM_PROG + r * 4, lane & 7);
        int slot = W_HEAD, ph = 0;
        int landed = 0, lslot = 0, lph = 0;
#pragma unroll 1
        for (int n = W_HEAD; n < kItems; n++) {
            if (n >= kNSlot) mbar_wait(bars + B_EMPTY + 8 * slot, ph ^ 1);
            if (HEAD_DT > 0 && n < N_HEAD) while ((SCHED_B ? (gt32() - t_start) * 2 : clock32() - t_start) < HEAD_T0 + (n - W_HEAD) * HEAD_DT) {}
            const int need = n - (n < N_HEAD && HEAD_DT == 0 ? W_HEAD : (n < N_TAIL ? W_MAIN : W_TAIL)) + 1;
            while (landed < need) {
                if (landed > n - kNSlot) mbar_wait(bars + B_FULL + 8 * lslot, lph);
                landed++;
                if (++lslot == kNSlot) { lslot = 0; lph ^= 1; }
            }
            if (SCHED_B) while ((int)(gt32() - t_start) < SCHED_A + n * SCHED_B + (n >= 68 ? SCHED_D : 0)) {}
            if (LEAD < kItems && n < kItems - PACE_END) {
                if (lane < 8) asm volatile("st.relaxed.cluster.shared::cluster.u32 [%0], %1;" ::"r"(prog_remote), "r"(n) : "memory");
                for (uint32_t it = 0;; it++) {
                    int p;
                    asm volatile("ld.relaxed.cluster.shared::cta.u32 %0, [%1];" : "=r"(p) : "r"(sb + SM_PROG + (lane & 7) * 4) : "memory");
                    if (__all_sync(0xffffffffu, max(p, W_HEAD) + LEAD >= n)) break;
                    if (it > kSpinLimit * 16) __trap();
                }
            }
            if (lane == 0) {
                const uint32_t fb = bars + B_FULL + 8 * slot, dst = sb + SM_RING + slot * kSlot;
                if (n < 4) {
                    if (W_HEAD <= 2 && n == 2) issue_w(2);
                    if (W_HEAD <= 3 && n == 3) issue_w(3);
                } else if ((unsigned)(n - kWoN) < 2u) {
                    const uint32_t wb = bars + B_W + 8 * (n - kWoN);
                    mbar_expect_tx(wb, kSlot);
                    tma4d(dst, &maps.m[5], r * 64, 0, 0, hkv * 32 + (n - kWoN) * 16, wb);
                    mbar_arrive(fb);
                } else {
                    const int u = n - (n < kWoN ? 4 : 6);
                    mbar_expect_tx(fb, kSlot);
                    tma3d<(EVF & 1) != 0>(dst, &maps.m[(u >> 3) & 1], 0, kvrow0 + ((((u >> 4) * 8 + (u & 7)) * ROT_M + rot) & 31) * 128, 0, fb);
                }
                if (n == GO_N) mbar_arrive(bars + B_GO);
            }
            __syncwarp();
            if (++slot == kNSlot) { slot = 0; ph ^= 1; }
        }
        TM(1);
    } else if (wid < 10) {
        const int kg = w >> 1, ch = w & 1;
        if (w == 7 && lane < 16) sts32(sb + SM_B1 + lane * 4, ldg32(b1 + hkv * 224 + (r < 7 ? r : 0) * 32 + 2 * lane));
        if (w == 6) sts128(sb + SM_H + g * 512 + 256 + (t >> 1) * 128 + (((6 + (t & 1)) ^ g) << 4), 0, 0, 0, 0);
        const uint32_t aoff = (r7 + 8 * (mi >> 1)) * 128 + (((4 * ch + (mi & 1)) ^ r7) << 4);
        bool early = false;
        cluster_wait();
#pragma unroll 1
        for (int pass = 0; pass < 4; pass++) {
            const bool big = pass == 0 || pass == 3;
            int slot = pass + 1, arow = kg * 64;
            uint32_t bbar = B_X, baddr = SM_XO + r7 * 1024, astep = 2048, ao = aoff;
            if (pass == 1) {
                arow = w * 32;
                baddr += ch * 512;
                astep = 1024;
                ao = (r7 + 8 * (mi >> 1)) * 64 + (((mi & 1) ^ (r7 >> 1)) << 4);
            } else if (pass == 2) {
                bbar = B_H;
                baddr = SM_H + r7 * 512;
            } else {
                slot = kg >> 1;
                arow = (kg & 1) * 128;
                if (pass == 3) { slot = slot ? (kWoN + 1) % kNSlot : kWoN % kNSlot; bbar = B_O; }
            }
            const uint32_t abar = pass == 3 ? B_W + 8 * (kg >> 1) : B_FULL + 8 * slot;
            const uint32_t abase = sb + SM_RING + slot * kSlot + arow * 128 + ao;
            baddr += sb + (mi >> 1) * 128 + (((2 * kg + (mi & 1)) ^ r7) << 4);
            bbar += bars;
            uint32_t wa = sb + SM_SCR + kg * 2176 + t * 544 + (ch * 32 + g) * 4;
            uint32_t* gp = &g_part[pass & 1][r][w][hkv][2 * lane];
            uint32_t ra = sb + SM_SCR + w * 272 + lane * 8;
            PIN(baddr); PIN(bbar); PIN(wa); PIN(ra); PINL(gp);
            uint32_t af[8][2][4];
            mbar_wait(bars + abar, 0);
#pragma unroll
            for (int ks = 0; ks < 4; ks++) {
                ldsm4t(af[ks][0], abase + ks * astep);
                ldsm4t(af[ks][1], (abase ^ 32) + ks * astep);
            }
            if (big) {
#pragma unroll
                for (int ks = 4; ks < 8; ks++) {
                    ldsm4t(af[ks][0], abase + ks * 2048);
                    ldsm4t(af[ks][1], (abase ^ 32) + ks * 2048);
                }
            }
            __syncwarp();
            if (lane == 0) mbar_arrive_n(bars + B_EMPTY + 8 * slot, big ? 2 : 1);
            if (pass == 2 && kg == 3) {
#pragma unroll
                for (int i = 0; i < 16; i++) af[2 + (i >> 3)][(i >> 2) & 1][i & 3] = 0u;
            }
            if (pass == 0) TM(2);
            TM(14);
            mbar_wait_cl(bbar, 0);
            TM(8);
            float acc[2][2][4];
#pragma unroll
            for (int i = 0; i < 16; i++) acc[i >> 3][(i >> 2) & 1][i & 3] = 0.f;
            uint32_t bf[4][4];
#pragma unroll
            for (int i = 0; i < 4; i++) ldsm4(bf[i], baddr + i * 256);
#pragma unroll
            for (int ks = 0; ks < 4; ks++) {
                mma16816(acc[0][ks & 1], af[ks][0], bf[ks >> 1][2 * (ks & 1)], bf[ks >> 1][2 * (ks & 1) + 1]);
                mma16816(acc[1][ks & 1], af[ks][1], bf[ks >> 1][2 * (ks & 1)], bf[ks >> 1][2 * (ks & 1) + 1]);
            }
            if (big) {
#pragma unroll
                for (int ks = 4; ks < 8; ks++) {
                    mma16816(acc[0][ks & 1], af[ks][0], bf[ks >> 1][2 * (ks & 1)], bf[ks >> 1][2 * (ks & 1) + 1]);
                    mma16816(acc[1][ks & 1], af[ks][1], bf[ks >> 1][2 * (ks & 1)], bf[ks >> 1][2 * (ks & 1) + 1]);
                }
            }
#pragma unroll
            for (int mt = 0; mt < 2; mt++) {
#pragma unroll
                for (int e = 0; e < 4; e++)
                    stsf(wa + (e & 1) * 272 + (mt * 16 + 8 * (e >> 1)) * 4, acc[mt][0][e] + acc[mt][1][e]);
            }
            bar_sync(1, 256);
            const float2 p0 = ldsf2(ra), p1 = ldsf2(ra + 2176), p2 = ldsf2(ra + 2 * 2176), p3 = ldsf2(ra + 3 * 2176);
            float s0 = (p0.x + p1.x) + (p2.x + p3.x), s1 = (p0.y + p1.y) + (p2.y + p3.y);
            st_rlx2_pred(gp, encf(s0), encf(s1), pass >= 2);
            TM(9);
            if (pass == 0) {
                const uint32_t rb = mapa(sb, w);
                st_async(rb + SM_Q + (r * 32 + lane) * 4, pack_bf16(s0, s1), rb + SM_BAR + B_Q);
                TM(3);
            } else if (pass == 1) {
                s0 += __shfl_xor_sync(0xffffffffu, s0, 16);
                s1 += __shfl_xor_sync(0xffffffffu, s1, 16);
                const uint32_t sw = pack_bf16(s0, s1), b1w = lds32(sb + SM_B1 + (lane & 15) * 4);
                const uint32_t vw = pack_bf16(bf_lo(sw) + bf_lo(b1w), bf_hi(sw) + bf_hi(b1w));
                const float v0 = bf_lo(vw), v1 = bf_hi(vw);
                const float c = 2.0f * 0.7978845608028654f;
                const uint32_t hw = pack_bf16(mul_sigmoid(v0, c * (v0 + 0.044715f * v0 * v0 * v0)),
                                              mul_sigmoid(v1, c * (v1 + 0.044715f * v1 * v1 * v1)));
                if (r < 7) {
                    const uint32_t ho = SM_H + w * 512 + (2 * (r & 1) + (mi & 1)) * 128 + (((2 * (r >> 1) + (r7 >> 2)) ^ w) << 4) + t * 4;
#pragma unroll
                    for (int d = 0; d < 4; d++) {
                        const uint32_t rb = mapa(sb, (lane >> 4) * 4 + d);
                        st_async(rb + ho, hw, rb + SM_BAR + B_H);
                    }
                }
            } else {
                uint32_t* src = &g_part[pass & 1][r][hkv][w][2 * lane];
                if (pass == 2) mbar_wait(bars + B_GO, 0);
                const uint32_t ga = sb + SM_G + w * 256 + lane * 8;
                for (uint32_t it = 0; !early; it++) {
                    early = gather_try(src, ga);
                    if (it > kSpinLimit) __trap();
                }
                bar_arrive(3, 288);
                *reinterpret_cast<uint2*>(src) = make_uint2(0u, 0u);
                TM(15);
                if (pass == 2) {
                    bar_sync(4, 288);
                    early = gather_try(src + 8 * kB * kHKV * 64, ga);
                }
            }
            if (pass < 2) bar_sync(1, 256);
        }
    } else {
        TMCAL();
        int slot = 4, ph = 0, u = 0;
        auto acquire = [&]() {
            if (u++ == WO_U) {
                slot += 2;
                if (slot >= kNSlot) { slot -= kNSlot; ph ^= 1; }
            }
            mbar_wait(bars + B_FULL + 8 * slot, ph);
            return sb + SM_RING + slot * kSlot;
        };
        auto release = [&]() {
            __syncwarp();
            if (lane == 0) mbar_arrive(bars + B_EMPTY + 8 * slot);
            if (++slot == kNSlot) { slot = 0; ph ^= 1; }
        };
        uint32_t koff[4];
#pragma unroll
        for (int c = 0; c < 4; c++)
            koff[c] = (w * 16 + r7 + 8 * (mi & 1)) * 128 + (((2 * c + (lane >> 4)) ^ r7) << 4);
        const uint32_t voff = (w >> 2) * 16384 + (r7 + 16 * (lane >> 4)) * 128 + (((2 * (w & 3) + (mi & 1)) ^ r7) << 4);
        const int ht = 2 * (t & 1) + (t >> 1);
        uint32_t ob = mapa(bars + B_O, 0), ostep = mapa(bars + B_O, 1) - ob;
        uint32_t oa = mapa(sb + SM_XO + r * 1024 + w * 128 + (((2 * ht + (g >> 2)) ^ r) << 4) + (g & 3) * 4, 0);
        PIN(oa); PIN(ob); PIN(ostep);
        cluster_wait();
        uint32_t qf[8][2];
        mbar_wait_cl(bars + B_Q, 0);
#pragma unroll
        for (int ks = 0; ks < 8; ks++) {
            qf[ks][0] = lds32(sb + SM_Q + ((g & 3) * 64 + ks * 8 + t) * 4);
            qf[ks][1] = lds32(sb + SM_Q + ((g & 3) * 64 + ks * 8 + 4 + t) * 4);
        }
        TM(4);
        uint32_t mx2 = 0xff80ff80u;
        uint32_t mprev = 0xff80ff80u;
        float Mw = -INFINITY, l = 0.f, fin = 0.f;
        float O[4][4];
#pragma unroll
        for (int i = 0; i < 4; i++) { O[i][0] = O[i][1] = O[i][2] = O[i][3] = 0.f; }
#pragma unroll 1
        for (int c = 0; c < 4; c++) {
            uint32_t pa = sb + SM_P + (g & 3) * kPStride + (lane >> 4) * 16 + t * 4 + w * 32;
#pragma unroll 1
            for (int it = 0; it < 8; it++) {
                const uint32_t base = acquire();
                float sa[4] = {0.f, 0.f, 0.f, 0.f}, sb2[4] = {0.f, 0.f, 0.f, 0.f};
                uint32_t kf[8][4];
#pragma unroll
                for (int ks = 0; ks < 8; ks++) ldsm4(kf[ks], base + (ks >> 2) * 16384 + koff[ks & 3]);
#pragma unroll
                for (int ks = 0; ks < 8; ks += 2) {
                    mma16816(sa, kf[ks], qf[ks][0], qf[ks][1]);
                    mma16816(sb2, kf[ks + 1], qf[ks + 1][0], qf[ks + 1][1]);
                }
                release();
                const float c0 = t < 2 ? sa[0] + sb2[0] : sa[2] + sb2[2];
                const float c1 = t < 2 ? sa[1] + sb2[1] : sa[3] + sb2[3];
                const float scale = 0.08838834764831845f;
                const uint32_t s2 = pack_bf16(c0, c1);
                const uint32_t v = pack_bf16(bf_lo(s2) * scale, bf_hi(s2) * scale);
                mx2 = max_bf16x2(mx2, v);
                sts32(pa, movm(v));
                pa += 256;
            }
            {
#pragma unroll
                for (int o = 2; o <= 16; o <<= 1) mx2 = max_bf16x2(mx2, __shfl_xor_sync(0xffffffffu, mx2, o));
                if (lane < 2) sts32(sb + SM_ML + lane * 32 + w * 4, mx2);
                bar_sync(2, 256);
                const uint4 a0 = lds128(sb + SM_ML), a1 = lds128(sb + SM_ML + 16);
                const uint4 b0 = lds128(sb + SM_ML + 32), b1v = lds128(sb + SM_ML + 48);
                const uint32_t m01 = max_bf16x2(max_bf16x2(max_bf16x2(a0.x, a0.y), max_bf16x2(a0.z, a0.w)),
                                                max_bf16x2(max_bf16x2(a1.x, a1.y), max_bf16x2(a1.z, a1.w)));
                const uint32_t m23 = max_bf16x2(max_bf16x2(max_bf16x2(b0.x, b0.y), max_bf16x2(b0.z, b0.w)),
                                                max_bf16x2(max_bf16x2(b1v.x, b1v.y), max_bf16x2(b1v.z, b1v.w)));
                const uint32_t mw = (w & 4) ? m23 : m01, mt = (t & 1) ? m23 : m01;
                const float M = (w & 2) ? bf_hi(mw) : bf_lo(mw);
                l *= ex2((Mw - M) * kLog2e);
                Mw = M;
                const float al0 = ex2((bf_lo(mprev) - bf_lo(mt)) * kLog2e), al1 = ex2((bf_hi(mprev) - bf_hi(mt)) * kLog2e);
                mprev = mt;
#pragma unroll
                for (int i = 0; i < 4; i++) { O[i][0] *= al0; O[i][1] *= al1; O[i][2] *= al0; O[i][3] *= al1; }
                const uint32_t ea = sb + SM_P + (w >> 1) * kPStride + (w & 1) * 1024 + lane * 16;
#pragma unroll
                for (int i = 0; i < 2; i++) {
                    const uint4 sv = lds128(ea + i * 512);
                    const uint32_t uu[4] = {sv.x, sv.y, sv.z, sv.w};
                    uint32_t rr[4];
#pragma unroll
                    for (int e = 0; e < 4; e++) {
                        const float p0 = ex2((bf_lo(uu[e]) - M) * kLog2e), p1 = ex2((bf_hi(uu[e]) - M) * kLog2e);
                        l += p0 + p1;
                        rr[e] = pack_bf16(p0, p1);
                    }
                    sts128(ea + i * 512, rr[0], rr[1], rr[2], rr[3]);
                }
                float ls = l;
#pragma unroll
                for (int o = 16; o; o >>= 1) ls += __shfl_xor_sync(0xffffffffu, ls, o);
                if (lane == 0) stsf(sb + SM_ML + 64 + w * 4, ls);
                bar_sync(2, 256);
                const float2 lp = ldsf2(sb + SM_ML + 64 + ht * 8);
                fin = __fdividef(1.0f, lp.x + lp.y);
                PINF(fin);
                if (c == 0) mbar_wait_cl(bars + B_H, 0);
                TM(5);
            }
            pa = sb + SM_P + (r7 & 3) * kPStride + (r7 >> 2) * 16 + mi * 32;
#pragma unroll 1
            for (int it = 0; it < 8; it++) {
                uint32_t pf[2][4];
                ldsm4(pf[0], pa);
                ldsm4(pf[1], pa + 128);
                pa += 256;
                const uint32_t base = acquire() + voff;
                uint32_t vf[8][4];
#pragma unroll
                for (int i = 0; i < 8; i++) ldsm4t(vf[i], base + (i >> 1) * 4096 + (i & 1) * 1024);
#pragma unroll
                for (int i = 0; i < 8; i++)
                    mma16816(O[i & 3], vf[i], pf[i >> 2][i & 2], pf[i >> 2][(i & 2) + 1]);
                release();
            }
        }
        TM(6);
        float v4[4];
#pragma unroll
        for (int e = 0; e < 4; e++) v4[e] = t < 2 ? O[0][e] + O[2][e] : O[1][e] + O[3][e];
        const float lo = (t < 2 ? v4[0] : v4[1]) + __shfl_xor_sync(0xffffffffu, t < 2 ? v4[1] : v4[0], 2);
        const float hi = (t < 2 ? v4[2] : v4[3]) + __shfl_xor_sync(0xffffffffu, t < 2 ? v4[3] : v4[2], 2);
        const uint32_t ow = pack_bf16(lo * fin, hi * fin);
#pragma unroll
        for (int d = 0; d < 8; d++) st_async(oa + d * ostep, ow, ob + d * ostep);
        TM(7);
    }
    TMDUMP();
}

typedef CUresult (*EncodeFn)(CUtensorMap*, CUtensorMapDataType, cuuint32_t, void*, const cuuint64_t*, const cuuint64_t*,
                             const cuuint32_t*, const cuuint32_t*, CUtensorMapInterleave, CUtensorMapSwizzle,
                             CUtensorMapL2promotion, CUtensorMapFloatOOBfill);

void encode(EncodeFn fn, CUtensorMap* m, void* p, int rank, const cuuint64_t* dims, const cuuint64_t* strides,
            const cuuint32_t* box, int promo, CUtensorMapSwizzle sw = CU_TENSOR_MAP_SWIZZLE_128B) {
    const cuuint32_t es[4] = {1, 1, 1, 1};
    fn(m, CU_TENSOR_MAP_DATA_TYPE_BFLOAT16, rank, p, dims, strides, box, es, CU_TENSOR_MAP_INTERLEAVE_NONE,
       sw, (CUtensorMapL2promotion)promo, CU_TENSOR_MAP_FLOAT_OOB_FILL_NONE);
}

}

extern "C" void kernel_launch(void* const* d_in, const int* in_sizes, int n_in, void* d_out, int out_size) {
    (void)in_sizes; (void)n_in; (void)out_size;
    void* fnp = nullptr;
    cudaDriverEntryPointQueryResult qr;
    cudaGetDriverEntryPoint("cuTensorMapEncodeTiled", &fnp, cudaEnableDefault, &qr);
    EncodeFn fn = (EncodeFn)fnp;
    Maps maps;
    {
        const cuuint64_t dims[3] = {64, (cuuint64_t)kB * kHKV * kSK, 2}, str[2] = {256, 128};
        const cuuint32_t box[3] = {64, 128, 2};
        encode(fn, &maps.m[0], d_in[1], 3, dims, str, box, PR_KV);
        encode(fn, &maps.m[1], d_in[2], 3, dims, str, box, PR_KV);
    }
    {
        const cuuint64_t dims[3] = {4096, 512, 1}, str[2] = {8192, 8192 * 512};
        const cuuint32_t box[3] = {64, 256, 1};
        encode(fn, &maps.m[2], d_in[3], 3, dims, str, box, PR_WQ);
    }
    {
        const cuuint64_t dims[3] = {1792, 256, 2}, str[2] = {3584, 3584 * 256};
        const cuuint32_t box[3] = {32, 256, 2};
        encode(fn, &maps.m[3], d_in[6], 3, dims, str, box, PR_W1, CU_TENSOR_MAP_SWIZZLE_64B);
    }
    {
        const cuuint64_t dims[3] = {512, 1792, 1}, str[2] = {1024, 1024 * 1792};
        const cuuint32_t box[3] = {64, 224, 1};
        encode(fn, &maps.m[4], d_in[8], 3, dims, str, box, PR_W2);
    }
    {
        const cuuint64_t dims[4] = {512, 2, 8, 256}, str[3] = {8 * 1024, 1024, 16 * 1024};
        const cuuint32_t box[4] = {64, 2, 8, 16};
        encode(fn, &maps.m[5], d_in[4], 4, dims, str, box, PR_WO);
    }
    cudaFuncSetAttribute(fused_decode_kernel, cudaFuncAttributeMaxDynamicSharedMemorySize, SM_BYTES);
    fused_decode_kernel<<<kGrid, kThreads, SM_BYTES>>>(
        (const __nv_bfloat16*)d_in[0], (const __nv_bfloat16*)d_in[7], (const __nv_bfloat16*)d_in[9],
        (__nv_bfloat16*)d_out, (const __nv_bfloat16*)d_in[3], maps);
}
```

```cpp
#include <cuda_runtime.h>
#include <cuda_bf16.h>
#include <cuda.h>
#include <stdint.h>

namespace {

constexpr int kB = 8, kD = 512, kHKV = 8, kSK = 4096;
constexpr int kGrid = 64, kFfnCtas = 0;
constexpr int kWarps = 14, kThreads = kWarps * 32;
constexpr int kSlot = 32768;
constexpr int kNSlot = 6;
constexpr int kItems = 70;
#define W_HEAD 3
#define N_HEAD 6
#define W_MAIN 4
#define LEAD 1
#define PACE_END 3
#define HEAD_T0 900
#define HEAD_DT 550
#define PR_KV 3
#define SCHED_B 660
#define SCHED_A (SCHED_E - 69 * SCHED_B)
#define SCHED_D 300
#define SCHED_E 43300
#define SCHED_D2 200
#define PFX 1
#define OGATE_T (OGATE_E - SCHED_D2)
#define OGATE_E 620
#define GO_N 40
constexpr int kW2N = 67, kWoN = 68;
static_assert(W_MAIN < kNSlot && W_MAIN >= 3 && W_HEAD == 3 && LEAD <= 2, "window");

constexpr int kPStride = 2048 + 32;
constexpr int SM_RING = 0;
constexpr int SM_H = kNSlot * kSlot;
constexpr int SM_XO = SM_H + 8 * 512;
constexpr int SM_P = SM_XO + 8 * 1024;
constexpr int SM_SCR = SM_P + 4 * kPStride;
constexpr int SM_Q = SM_SCR + 4 * 2176;
constexpr int SM_G = SM_Q + 1024;
constexpr int SM_ML = SM_G + 2048;
constexpr int SM_B1 = SM_ML + 128;
constexpr int SM_PROG = SM_B1 + 64;
constexpr int SM_BAR = SM_PROG + 32;
constexpr int B_FULL = 0, B_EMPTY = 8 * kNSlot, B_W = 16 * kNSlot, B_GO = B_W + 40, B_GO2 = B_GO + 8, B_X = B_GO2 + 8, B_Q = B_X + 8,
              B_Y = B_Q + 8, B_S = B_Y + 8, B_H = B_S + 8, B_END = B_H + 8;
constexpr int SM_TM = SM_BAR + B_END;
constexpr int SM_END = SM_TM;
constexpr int SM_BYTES = SM_END + 1024;
static_assert(SM_BYTES <= 232448, "smem");

constexpr float kLog2e = 1.4426950408889634f;
constexpr uint32_t kSpinLimit = 1u << 22;
constexpr long long kWaitCycles = 1ll << 32;

struct Maps { CUtensorMap m[6]; const char* p[6]; };

__device__ __align__(128) uint32_t g_o[8][kHKV][2048];
__device__ __align__(128) uint32_t g_h[8][8][1024];

#define TM(i)
#define TMDUMP()
#define TMCAL()

__device__ __forceinline__ uint32_t smem_u32(const void* p) { return (uint32_t)__cvta_generic_to_shared(p); }
__device__ __forceinline__ void mbar_init(uint32_t bar, uint32_t cnt) {
    asm volatile("mbarrier.init.shared::cta.b64 [%0], %1;" ::"r"(bar), "r"(cnt) : "memory");
}
__device__ __forceinline__ void mbar_expect_tx(uint32_t bar, uint32_t bytes) {
    asm volatile("mbarrier.arrive.expect_tx.shared::cta.b64 _, [%0], %1;" ::"r"(bar), "r"(bytes) : "memory");
}
__device__ __forceinline__ void mbar_arrive(uint32_t bar) {
    asm volatile("mbarrier.arrive.shared::cta.b64 _, [%0];" ::"r"(bar) : "memory");
}
__device__ __forceinline__ void mbar_arrive_n(uint32_t bar, uint32_t n) {
    asm volatile("mbarrier.arrive.shared::cta.b64 _, [%0], %1;" ::"r"(bar), "r"(n) : "memory");
}
__device__ __forceinline__ bool mbar_try(uint32_t bar, uint32_t parity) {
    uint32_t ok;
    asm volatile("{\n.reg .pred p;\nmbarrier.try_wait.parity.relaxed.cluster.shared::cta.b64 p, [%1], %2;\nselp.u32 %0, 1, 0, p;\n}"
                 : "=r"(ok) : "r"(bar), "r"(parity) : "memory");
    return ok != 0u;
}
__device__ __forceinline__ bool mbar_try_cta(uint32_t bar, uint32_t parity) {
    uint32_t ok;
    asm volatile("{\n.reg .pred p;\nmbarrier.try_wait.parity.shared::cta.b64 p, [%1], %2;\nselp.u32 %0, 1, 0, p;\n}"
                 : "=r"(ok) : "r"(bar), "r"(parity) : "memory");
    return ok != 0u;
}
__device__ __forceinline__ bool mbar_test(uint32_t bar, uint32_t parity) {
    uint32_t ok;
    asm volatile("{\n.reg .pred p;\nmbarrier.test_wait.parity.shared::cta.b64 p, [%1], %2;\nselp.u32 %0, 1, 0, p;\n}"
                 : "=r"(ok) : "r"(bar), "r"(parity) : "memory");
    return ok != 0u;
}
__device__ __forceinline__ void mbar_wait(uint32_t bar, uint32_t parity) {
    if (mbar_try_cta(bar, parity)) return;
    const long long t0 = clock64();
    while (!mbar_try_cta(bar, parity))
        if (clock64() - t0 > kWaitCycles) __trap();
}
__device__ __forceinline__ void mbar_wait_cl(uint32_t bar, uint32_t parity) {
    if (!mbar_try(bar, parity)) {
        const long long t0 = clock64();
        while (!mbar_try(bar, parity))
            if (clock64() - t0 > kWaitCycles) __trap();
    }
    asm volatile("fence.acquire.sync_restrict::shared::cluster.cluster;" ::: "memory");
}
#define PIN(x) asm volatile("shfl.sync.bfly.b32 %0, %0, 0, 0x1f, 0xffffffff;" : "+r"(x) :: "memory")
#define PINF(x) asm volatile("" : "+f"(x) :: "memory")
#define PINL(x) asm volatile("{\n.reg .b32 lo, hi;\nmov.b64 {lo, hi}, %0;\nshfl.sync.bfly.b32 lo, lo, 0, 0x1f, 0xffffffff;\n" \
                             "shfl.sync.bfly.b32 hi, hi, 0, 0x1f, 0xffffffff;\nmov.b64 %0, {lo, hi};\n}" : "+l"(x) :: "memory")
#define EVF 1
constexpr uint64_t kEvictFirst = 0x12F0000000000000ull;
__device__ __forceinline__ void tma4d(uint32_t dst, const CUtensorMap* m, int c0, int c1, int c2, int c3, uint32_t bar) {
    asm volatile("cp.async.bulk.tensor.4d.shared::cluster.global.mbarrier::complete_tx::bytes [%0], [%1, {%3, %4, %5, %6}], [%2];"
                 ::"r"(dst), "l"(m), "r"(bar), "r"(c0), "r"(c1), "r"(c2), "r"(c3) : "memory");
}
template <bool kHint>
__device__ __forceinline__ void tma3d(uint32_t dst, const CUtensorMap* m, int c0, int c1, int c2, uint32_t bar) {
    if (kHint)
        asm volatile("cp.async.bulk.tensor.3d.shared::cluster.global.mbarrier::complete_tx::bytes.L2::cache_hint [%0], [%1, {%3, %4, %5}], [%2], %6;"
                     ::"r"(dst), "l"(m), "r"(bar), "r"(c0), "r"(c1), "r"(c2), "l"(kEvictFirst) : "memory");
    else
        asm volatile("cp.async.bulk.tensor.3d.shared::cluster.global.mbarrier::complete_tx::bytes [%0], [%1, {%3, %4, %5}], [%2];"
                     ::"r"(dst), "l"(m), "r"(bar), "r"(c0), "r"(c1), "r"(c2) : "memory");
}
__device__ __forceinline__ void bar_sync(int id, int n) { asm volatile("barrier.sync %0, %1;" ::"r"(id), "r"(n) : "memory"); }
__device__ __forceinline__ void bar_arrive(int id, int n) { asm volatile("barrier.arrive %0, %1;" ::"r"(id), "r"(n) : "memory"); }
__device__ __forceinline__ bool elect_one() {
    uint32_t p;
    asm volatile("{\n.reg .pred p;\nelect.sync _|p, 0xffffffff;\nselp.u32 %0, 1, 0, p;\n}" : "=r"(p));
    return p != 0u;
}
__device__ __forceinline__ void cluster_arrive() { asm volatile("barrier.cluster.arrive.relaxed;" ::: "memory"); }
__device__ __forceinline__ void cluster_wait() { asm volatile("barrier.cluster.wait;" ::: "memory"); }
__device__ __forceinline__ uint32_t mapa(uint32_t a, uint32_t rank) {
    uint32_t d;
    asm("mapa.shared::cluster.u32 %0, %1, %2;" : "=r"(d) : "r"(a), "r"(rank));
    return d;
}
__device__ __forceinline__ void st_async(uint32_t a, uint32_t v, uint32_t bar) {
    asm volatile("st.async.shared::cluster.mbarrier::complete_tx::bytes.u32 [%0], %1, [%2];" ::"r"(a), "r"(v), "r"(bar) : "memory");
}
__device__ __forceinline__ void st_async_pred(uint32_t a, float x, uint32_t bar, bool c) {
    asm volatile("{\n.reg .pred p;\nsetp.ne.u32 p, %3, 0;\n@p st.async.shared::cluster.mbarrier::complete_tx::bytes.f32 [%0], %1, [%2];\n}"
                 ::"r"(a), "f"(x), "r"(bar), "r"((uint32_t)c) : "memory");
}
__device__ __forceinline__ void st_async2_pred(uint32_t a, float x, float y, uint32_t bar, bool c) {
    asm volatile("{\n.reg .pred p;\nsetp.ne.u32 p, %4, 0;\n@p st.async.shared::cluster.mbarrier::complete_tx::bytes.v2.f32 [%0], {%1,%2}, [%3];\n}"
                 ::"r"(a), "f"(x), "f"(y), "r"(bar), "r"((uint32_t)c) : "memory");
}
__device__ __forceinline__ void st_async4(uint32_t a, uint32_t x, uint32_t y, uint32_t z, uint32_t w, uint32_t bar) {
    asm volatile("st.async.shared::cluster.mbarrier::complete_tx::bytes.v4.u32 [%0], {%1,%2,%3,%4}, [%5];"
                 ::"r"(a), "r"(x), "r"(y), "r"(z), "r"(w), "r"(bar) : "memory");
}

__device__ __forceinline__ void ldsm4(uint32_t (&r)[4], uint32_t a) {
    asm volatile("ldmatrix.sync.aligned.m8n8.x4.shared.b16 {%0,%1,%2,%3}, [%4];"
                 : "=r"(r[0]), "=r"(r[1]), "=r"(r[2]), "=r"(r[3]) : "r"(a) : "memory");
}
__device__ __forceinline__ void ldsm4t(uint32_t (&r)[4], uint32_t a) {
    asm volatile("ldmatrix.sync.aligned.m8n8.x4.trans.shared.b16 {%0,%1,%2,%3}, [%4];"
                 : "=r"(r[0]), "=r"(r[1]), "=r"(r[2]), "=r"(r[3]) : "r"(a) : "memory");
}
__device__ __forceinline__ void mma16816(float (&c)[4], const uint32_t (&a)[4], uint32_t b0, uint32_t b1) {
    asm volatile("mma.sync.aligned.m16n8k16.row.col.f32.bf16.bf16.f32 {%0,%1,%2,%3}, {%4,%5,%6,%7}, {%8,%9}, {%0,%1,%2,%3};"
                 : "+f"(c[0]), "+f"(c[1]), "+f"(c[2]), "+f"(c[3])
                 : "r"(a[0]), "r"(a[1]), "r"(a[2]), "r"(a[3]), "r"(b0), "r"(b1));
}
__device__ __forceinline__ uint32_t movm(uint32_t a) {
    uint32_t d;
    asm volatile("movmatrix.sync.aligned.m8n8.trans.b16 %0, %1;" : "=r"(d) : "r"(a));
    return d;
}
__device__ __forceinline__ uint32_t pack_bf16(float lo, float hi) {
    uint32_t d;
    asm("cvt.rn.bf16x2.f32 %0, %1, %2;" : "=r"(d) : "f"(hi), "f"(lo));
    return d;
}
__device__ __forceinline__ float bf_lo(uint32_t u) { return __uint_as_float(u << 16); }
__device__ __forceinline__ float bf_hi(uint32_t u) { return __uint_as_float(u & 0xffff0000u); }
__device__ __forceinline__ float bfr(float v) { return __uint_as_float(pack_bf16(0.f, v)); }
__device__ __forceinline__ uint32_t max_bf16x2(uint32_t a, uint32_t b) {
    uint32_t d;
    asm("max.bf16x2 %0, %1, %2;" : "=r"(d) : "r"(a), "r"(b));
    return d;
}
__device__ __forceinline__ float ex2(float x) {
    float y;
    asm("ex2.approx.ftz.f32 %0, %1;" : "=f"(y) : "f"(x));
    return y;
}
__device__ __forceinline__ float mul_sigmoid(float v, float z) { return __fdividef(v, 1.0f + ex2(fminf(-kLog2e * z, 120.f))); }
__device__ __forceinline__ uint32_t lds32(uint32_t a) { uint32_t v; asm volatile("ld.shared.u32 %0, [%1];" : "=r"(v) : "r"(a) : "memory"); return v; }
__device__ __forceinline__ float2 ldsf2(uint32_t a) { float2 v; asm volatile("ld.shared.v2.f32 {%0,%1}, [%2];" : "=f"(v.x), "=f"(v.y) : "r"(a) : "memory"); return v; }
__device__ __forceinline__ uint4 lds128(uint32_t a) {
    uint4 v;
    asm volatile("ld.shared.v4.u32 {%0,%1,%2,%3}, [%4];" : "=r"(v.x), "=r"(v.y), "=r"(v.z), "=r"(v.w) : "r"(a) : "memory");
    return v;
}
__device__ __forceinline__ void sts32(uint32_t a, uint32_t v) { asm volatile("st.shared.u32 [%0], %1;" ::"r"(a), "r"(v) : "memory"); }
__device__ __forceinline__ void stsf(uint32_t a, float v) { asm volatile("st.shared.f32 [%0], %1;" ::"r"(a), "f"(v) : "memory"); }
__device__ __forceinline__ void sts128(uint32_t a, uint32_t x, uint32_t y, uint32_t z, uint32_t w) {
    asm volatile("st.shared.v4.u32 [%0], {%1,%2,%3,%4};" ::"r"(a), "r"(x), "r"(y), "r"(z), "r"(w) : "memory");
}
__device__ __forceinline__ uint32_t encf(float v) { const uint32_t b = __float_as_uint(v); return b == 0u ? 0x80000000u : b; }
__device__ __forceinline__ void st_rlx2_pred(uint32_t* p, uint32_t a, uint32_t b, bool c) {
    asm volatile("{\n.reg .pred p;\nsetp.ne.u32 p, %3, 0;\n@p st.relaxed.gpu.global.v2.u32 [%0], {%1,%2};\n}" ::"l"(p), "r"(a), "r"(b), "r"((uint32_t)c) : "memory");
}
__device__ __forceinline__ void st_pred32(void* p, uint32_t v, bool c) {
    asm volatile("{\n.reg .pred p;\nsetp.ne.u32 p, %2, 0;\n@p st.global.u32 [%0], %1;\n}" ::"l"(p), "r"(v), "r"((uint32_t)c) : "memory");
}
__device__ __forceinline__ void ld_rlx2_pred(uint2& v, const uint32_t* p, bool c) {
    asm volatile("{\n.reg .pred p;\nsetp.ne.u32 p, %3, 0;\n@p ld.relaxed.gpu.global.v2.u32 {%0,%1}, [%2];\n}"
                 : "+r"(v.x), "+r"(v.y) : "l"(p), "r"((uint32_t)c) : "memory");
}
__device__ __forceinline__ void ld_rlx4_pred(uint32_t (&v)[4], const uint32_t* p, bool c) {
    asm volatile("{\n.reg .pred p;\nsetp.ne.u32 p, %5, 0;\n@p ld.relaxed.gpu.global.v4.u32 {%0,%1,%2,%3}, [%4];\n}"
                 : "+r"(v[0]), "+r"(v[1]), "+r"(v[2]), "+r"(v[3]) : "l"(p), "r"((uint32_t)c) : "memory");
}
__device__ __forceinline__ uint2 ld_rlx2(const uint32_t* p) {
    uint2 v;
    asm volatile("ld.relaxed.gpu.global.v2.u32 {%0,%1}, [%2];" : "=r"(v.x), "=r"(v.y) : "l"(p) : "memory");
    return v;
}
__device__ __forceinline__ uint32_t clock32() { uint32_t c; asm volatile("mov.u32 %0, %clock;" : "=r"(c) :: "memory"); return c; }
__device__ __forceinline__ uint32_t gt32() { uint32_t c; asm volatile("mov.u32 %0, %globaltimer_lo;" : "=r"(c) :: "memory"); return c; }
__device__ __forceinline__ uint32_t ldg32(const void* p) {
    uint32_t v;
    asm volatile("ld.global.nc.u32 %0, [%1];" : "=r"(v) : "l"(p));
    return v;
}

__global__ void __cluster_dims__(8, 1, 1) __launch_bounds__(kThreads, 1)
fused_decode_kernel(const __nv_bfloat16* __restrict__ x, const __nv_bfloat16* __restrict__ b1,
                    const __nv_bfloat16* __restrict__ b2, __nv_bfloat16* __restrict__ out,
                    const __grid_constant__ Maps maps) {
    extern __shared__ __align__(1024) unsigned char smem_raw[];
    const uint32_t sb = (smem_u32(smem_raw) + 1023u) & ~1023u;
    const uint32_t bars = sb + SM_BAR;
    const int tid = threadIdx.x, wid = tid >> 5, lane = tid & 31;
    const int hkv = blockIdx.x >> 3, r = blockIdx.x & 7;

    TM(0);
    auto issue_w = [&](int n) {
        const uint32_t bar = bars + B_FULL + 8 * n, dst = sb + SM_RING + n * kSlot;
        if (n < 2) {
            mbar_expect_tx(bar, kSlot);
            tma3d<(EVF & 2) != 0>(dst, &maps.m[2], blockIdx.x * 64, n * 256, 0, bar);
        } else {
            mbar_expect_tx(bar, r < 7 ? kSlot : 0);
            if (r < 7) tma3d<(EVF & 2) != 0>(dst, &maps.m[3], hkv * 224 + r * 32, 0, 0, bar);
        }
    };
    if (tid < 32) {
        if (elect_one()) {
            mbar_init(bars + B_FULL, 1);
            mbar_init(bars + B_FULL + 8, 1);
            asm volatile("fence.mbarrier_init.release.cluster;" ::: "memory");
            issue_w(0);
            issue_w(1);
#pragma unroll
            for (int n = 2; n < kNSlot; n++) mbar_init(bars + B_FULL + 8 * n, 1);
            asm volatile("fence.mbarrier_init.release.cluster;" ::: "memory");
#pragma unroll
            for (int n = 2; n < W_HEAD; n++) issue_w(n);
        }
    }
    if (wid == 1) asm volatile("prefetch.global.L1 [%0];" ::"l"(x + r * kD + lane * 16) : "memory");
    if (wid == 3) {
        if ((PFX & 1) && lane < 6 && lane != 2 && lane != 3) asm volatile("prefetch.tensormap [%0];" ::"l"(&maps.m[lane]) : "memory");
        if ((PFX & 2) && lane >= 8 && lane < 12) {
            const char* pp = lane < 10 ? maps.p[lane - 8] + (size_t)(r * kHKV + hkv) * kSK * 256
                           : lane == 10 ? maps.p[4] + (size_t)(r * 224) * 1024 + hkv * 128 : maps.p[5] + (size_t)(hkv * 512) * 1024 + r * 128;
            asm volatile("prefetch.global.L2 [%0];" ::"l"(pp) : "memory");
        }
    }
    const uint32_t t_start = gt32();
    if (tid == 64) {
#pragma unroll
        for (int n = 0; n < kNSlot; n++) mbar_init(bars + B_EMPTY + 8 * n, 8);
#pragma unroll
        for (int n = B_W; n < B_END; n += 8) mbar_init(bars + n, n < B_H ? 1 : 8);
        asm volatile("fence.mbarrier_init.release.cluster;" ::: "memory");
        sts128(sb + SM_PROG, 0, 0, 0, 0);
        sts128(sb + SM_PROG + 16, 0, 0, 0, 0);
        asm volatile("fence.release.sync_restrict::shared::cta.cluster;" ::: "memory");
        mbar_expect_tx(bars + B_X, 8192);
        mbar_expect_tx(bars + B_Q, 1024);
        mbar_expect_tx(bars + B_Y, 2048);
        mbar_expect_tx(bars + B_S, 2048);
    }
    __syncwarp();
    cluster_arrive();
    TM(11);
    const int w = (wid - 2) & 7;
    const int g = lane >> 2, t = lane & 3, r7 = lane & 7, mi = lane >> 3;

    if (wid == 1) {
        {
            const uint4* xr = reinterpret_cast<const uint4*>(x + r * kD) + lane;
            const uint4 xv0 = __ldg(xr), xv1 = __ldg(xr + 32);
            float f[16];
            const uint32_t u[8] = {xv0.x, xv0.y, xv0.z, xv0.w, xv1.x, xv1.y, xv1.z, xv1.w};
#pragma unroll
            for (int i = 0; i < 8; i++) { f[2 * i] = bf_lo(u[i]); f[2 * i + 1] = bf_hi(u[i]); }
            float s = 0.f;
#pragma unroll
            for (int i = 0; i < 16; i++) s += f[i];
#pragma unroll
            for (int o = 16; o; o >>= 1) s += __shfl_xor_sync(0xffffffffu, s, o);
            const float mean = s * (1.0f / kD);
            float vs = 0.f;
#pragma unroll
            for (int i = 0; i < 16; i++) { const float d = f[i] - mean; vs = fmaf(d, d, vs); }
#pragma unroll
            for (int o = 16; o; o >>= 1) vs += __shfl_xor_sync(0xffffffffu, vs, o);
            const float mb = bfr(mean);
            const float den = bfr(__fsqrt_rn(bfr(bfr(vs * (1.0f / kD)) + 1e-5f)));
            const float rden = __frcp_rn(den);
            uint32_t q[8];
#pragma unroll
            for (int i = 0; i < 8; i++) {
                const uint32_t d2 = pack_bf16(f[2 * i] - mb, f[2 * i + 1] - mb);
                q[i] = pack_bf16(bf_lo(d2) * rden, bf_hi(d2) * rden);
            }
            const uint32_t xoff = SM_XO + r * 1024 + ((lane >> 1) & 7) * 128 + (((2 * (lane >> 4) + (lane & 1)) ^ r) << 4);
            cluster_wait();
#pragma unroll 1
            for (int d = 0; d < 8; d++) {
                const uint32_t rb = mapa(sb, d), xa = rb + xoff;
                st_async4(xa, q[0], q[1], q[2], q[3], rb + SM_BAR + B_X);
                st_async4(xa ^ 64, q[4], q[5], q[6], q[7], rb + SM_BAR + B_X);
            }
        }
        const int col = hkv * 64 + 2 * lane;
        const uint32_t xw = ldg32(x + r * kD + col), bw = ldg32(b2 + col);
        __nv_bfloat16* dst = out + r * kD + col;
        uint32_t pa = sb + SM_G + lane * 8, pbar = bars + B_Y;
        PINL(dst);
        float g0 = 0.f, g1 = 0.f;
#pragma unroll 1
        for (int pass = 0; pass < 2; pass++) {
            mbar_wait_cl(pbar, 0);
            TM(15);
            float2 v[8];
#pragma unroll
            for (int c = 0; c < 8; c++) v[c] = ldsf2(pa + c * 256);
            const uint32_t sw = pack_bf16(((v[0].x + v[1].x) + (v[2].x + v[3].x)) + ((v[4].x + v[5].x) + (v[6].x + v[7].x)),
                                          ((v[0].y + v[1].y) + (v[2].y + v[3].y)) + ((v[4].y + v[5].y) + (v[6].y + v[7].y)));
            const uint32_t pw = pack_bf16(bf_lo(sw) * g0, bf_hi(sw) * g1);
            st_pred32(dst, pack_bf16(bf_lo(xw) + bf_lo(pw), bf_hi(xw) + bf_hi(pw)), pass);
            if (pass) break;
            TM(2);
            const uint32_t yw = pack_bf16(bf_lo(sw) + bf_lo(bw), bf_hi(sw) + bf_hi(bw));
            const uint32_t gw = pack_bf16(mul_sigmoid(bf_lo(yw), bf_lo(yw)), mul_sigmoid(bf_hi(yw), bf_hi(yw)));
            g0 = bf_lo(gw);
            g1 = bf_hi(gw);
            pa = sb + SM_XO + lane * 8;
            pbar = bars + B_S;
        }
        TM(10);
    } else if (wid == 0) {
        cluster_wait();
        const int kvrow0 = (r * kHKV + hkv) * kSK;
        const uint32_t prog_remote = mapa(sb + SM_PROG + r * 4, lane & 7);
        int slot = W_HEAD, ph = 0;
        int lslot = 0, lph = 0;
#pragma unroll 1
        for (int n = W_HEAD; n < kItems; n++) {
            if (n >= kNSlot) mbar_wait(bars + B_EMPTY + 8 * slot, ph ^ 1);
            if (n >= W_MAIN) {
                mbar_wait(bars + B_FULL + 8 * lslot, lph);
                if (++lslot == kNSlot) { lslot = 0; lph ^= 1; }
            }
            const int due = n < N_HEAD ? HEAD_T0 + (n - W_HEAD) * HEAD_DT : SCHED_A + n * SCHED_B + (n >= kW2N ? (n >= kWoN ? SCHED_D2 : SCHED_D) : 0);
            while ((int)(gt32() - t_start) < due) {}
            if (LEAD < kItems && n < kItems - PACE_END) {
                if (lane < 8) asm volatile("st.relaxed.cluster.shared::cluster.u32 [%0], %1;" ::"r"(prog_remote), "r"(n) : "memory");
                for (uint32_t it = 0;; it++) {
                    int p;
                    asm volatile("ld.relaxed.cluster.shared::cta.u32 %0, [%1];" : "=r"(p) : "r"(sb + SM_PROG + (lane & 7) * 4) : "memory");
                    if (__all_sync(0xffffffffu, max(p, W_HEAD) + LEAD >= n)) break;
                    if (it > kSpinLimit * 16) __trap();
                }
            }
            if (elect_one()) {
                const uint32_t fb = bars + B_FULL + 8 * slot, dst = sb + SM_RING + slot * kSlot;
                if (n < kW2N) {
                    const int u = n - 3;
                    mbar_expect_tx(fb, kSlot);
                    tma3d<(EVF & 1) != 0>(dst, &maps.m[(u >> 3) & 1], 0, kvrow0 + (u >> 4) * 1024 + (u & 7) * 128, 0, fb);
                } else if (n >= kWoN) {
                    const uint32_t wb = bars + B_W + 16 * (n - kWoN);
                    mbar_expect_tx(wb, kSlot / 2);
                    tma4d(dst, &maps.m[5], hkv * 64, 0, 0, r * 32 + (n - kWoN) * 16, wb);
                    mbar_expect_tx(wb + 8, kSlot / 2);
                    tma4d(dst + kSlot / 2, &maps.m[5], hkv * 64, 0, 0, r * 32 + (n - kWoN) * 16 + 8, wb + 8);
                } else {
                    mbar_expect_tx(bars + B_W + 32, 224 * 128);
                    tma3d<false>(dst, &maps.m[4], hkv * 64, r * 224, 0, bars + B_W + 32);
                }
                if (n == GO_N) mbar_arrive(bars + B_GO);
            }
            __syncwarp();
            if (++slot == kNSlot) { slot = 0; ph ^= 1; }
        }
        TM(1);
        const uint32_t t_last = gt32();
        while ((int)(gt32() - t_last) < OGATE_T) {}
        if (lane == 0) mbar_arrive(bars + B_GO2);
    } else if (wid < 10) {
        const int kg = w >> 1, ch = w & 1;
        if (w == 7 && lane < 16) sts32(sb + SM_B1 + lane * 4, ldg32(b1 + hkv * 224 + (r < 7 ? r : 0) * 32 + 2 * lane));
        uint32_t wa = sb + SM_SCR + kg * 2176 + t * 544 + (ch * 32 + g) * 4;
        uint32_t ra = sb + SM_SCR + w * 272 + lane * 8;
        uint32_t* op = &g_o[hkv][r][kg * 512 + lane * 4];
        const uint32_t baddr = sb + SM_XO + r7 * 1024 + (mi & 1) * 128 + (((2 * kg + (mi >> 1)) ^ r7) << 4);
        uint32_t abase = sb + SM_RING + kg * (kSlot / 2) + (r7 + 16 * (mi >> 1)) * 128 + (((4 * ch + (mi & 1)) ^ r7) << 4);
        uint32_t abar = bars + B_FULL + 8 * (kg >> 1);
        uint32_t sa = mapa(sb + SM_XO + r * 256 + lane * 8, w), sbar = mapa(bars + B_S, w);
        PIN(wa); PIN(ra); PINL(op); PIN(sa); PIN(sbar);
        uint32_t bf[4][4];
        auto fetch_o = [&]() {
            bool all = true;
#pragma unroll
            for (int j = 0; j < 4; j++) {
                const bool ok = bf[j][0] != 0u && bf[j][1] != 0u && bf[j][2] != 0u && bf[j][3] != 0u;
                all = all && ok;
                ld_rlx4_pred(bf[j], op + j * 128, !ok);
            }
            return __all_sync(0xffffffffu, all);
        };
        cluster_wait();
        mbar_wait_cl(bars + B_X, 0);
#pragma unroll 1
        for (int pass = 0; pass < 3; pass++) {
            float acc[2][2][4];
#pragma unroll
            for (int i = 0; i < 16; i++) acc[i >> 3][(i >> 2) & 1][i & 3] = 0.f;
            bool stream = true;
            if (pass == 2) {
                mbar_wait(bars + B_GO2, 0);
                for (uint32_t it = 0;; it++) {
                    stream = fetch_o();
                    if (stream || __all_sync(0xffffffffu, mbar_test(abar, 0))) break;
                    if (it > kSpinLimit) __trap();
                }
            } else {
#pragma unroll
                for (int i = 0; i < 4; i++) ldsm4(bf[i], baddr + ((i * 256 + (pass & ch) * 512) & 1023));
            }
            if (pass == 1) {
                const uint32_t a1 = sb + SM_RING + 2 * kSlot + w * 4096 + (r7 + 16 * (mi >> 1)) * 64 + (((mi & 1) ^ (r7 >> 1)) << 4);
                mbar_wait(bars + B_FULL + 16, 0);
#pragma unroll
                for (int ks = 0; ks < 4; ks++) {
#pragma unroll
                    for (int mt = 0; mt < 2; mt++) {
                        uint32_t af[4];
                        ldsm4t(af, (a1 ^ (mt * 32)) + (ks >> 1) * 2048 + (ks & 1) * 512);
                        mma16816(acc[mt][ks & 1], af, bf[ks >> 1][2 * (ks & 1)], bf[ks >> 1][2 * (ks & 1) + 1]);
                    }
                }
            } else if (stream) {
                TM(8);
                mbar_wait(abar, 0);
                TM(14);
#pragma unroll
                for (int ks = 0; ks < 8; ks++) {
#pragma unroll
                    for (int mt = 0; mt < 2; mt++) {
                        uint32_t af[4];
                        ldsm4t(af, (abase ^ (mt * 32)) + (ks >> 1) * 4096 + (ks & 1) * 1024);
                        mma16816(acc[mt][ks & 1], af, bf[ks >> 1][2 * (ks & 1)], bf[ks >> 1][2 * (ks & 1) + 1]);
                    }
                }
            } else {
                uint32_t af[8][2][4];
                mbar_wait(abar, 0);
                TM(14);
#pragma unroll
                for (int ks = 0; ks < 8; ks++) {
                    ldsm4t(af[ks][0], abase + (ks >> 1) * 4096 + (ks & 1) * 1024);
                    ldsm4t(af[ks][1], (abase ^ 32) + (ks >> 1) * 4096 + (ks & 1) * 1024);
                }
                for (uint32_t it = 0; !fetch_o(); it++)
                    if (it > kSpinLimit) __trap();
                TM(8);
#pragma unroll
                for (int ks = 0; ks < 8; ks++) {
                    mma16816(acc[0][ks & 1], af[ks][0], bf[ks >> 1][2 * (ks & 1)], bf[ks >> 1][2 * (ks & 1) + 1]);
                    mma16816(acc[1][ks & 1], af[ks][1], bf[ks >> 1][2 * (ks & 1)], bf[ks >> 1][2 * (ks & 1) + 1]);
                }
            }
#pragma unroll
            for (int mt = 0; mt < 2; mt++) {
#pragma unroll
                for (int e = 0; e < 4; e++)
                    stsf(wa + (e & 1) * 272 + (mt * 16 + 8 * (e >> 1)) * 4, acc[mt][0][e] + acc[mt][1][e]);
            }
            bar_sync(1, 256);
            const float2 p0 = ldsf2(ra), p1 = ldsf2(ra + 2176), p2 = ldsf2(ra + 2 * 2176), p3 = ldsf2(ra + 3 * 2176);
            float s0 = (p0.x + p1.x) + (p2.x + p3.x), s1 = (p0.y + p1.y) + (p2.y + p3.y);
            st_async2_pred(sa, s0, s1, sbar, pass == 2);
            TM(9);
            if (pass == 2) break;
            if (pass == 0) {
                const uint32_t rb = mapa(sb, w);
                st_async(rb + SM_Q + (r * 32 + lane) * 4, pack_bf16(s0, s1), rb + SM_BAR + B_Q);
                if (lane == 0) mbar_arrive_n(bars + B_EMPTY + 8 * (kg >> 1), 2);
                TM(3);
            } else if (pass == 1) {
                if (lane == 0) mbar_arrive(bars + B_EMPTY + 16);
                s0 += __shfl_xor_sync(0xffffffffu, s0, 16);
                s1 += __shfl_xor_sync(0xffffffffu, s1, 16);
                const uint32_t sw = pack_bf16(s0, s1), b1w = lds32(sb + SM_B1 + (lane & 15) * 4);
                const uint32_t vw = pack_bf16(bf_lo(sw) + bf_lo(b1w), bf_hi(sw) + bf_hi(b1w));
                const float v0 = bf_lo(vw), v1 = bf_hi(vw);
                const float c = 2.0f * 0.7978845608028654f;
                uint32_t hw = pack_bf16(mul_sigmoid(v0, c * (v0 + 0.044715f * v0 * v0 * v0)),
                                        mul_sigmoid(v1, c * (v1 + 0.044715f * v1 * v1 * v1)));
                hw = r < 7 ? encf(__uint_as_float(hw)) : 0x80000000u;
                {
                    uint32_t* cp = &g_o[w][hkv][(g * 16 + r) * 16 + t * 4];
                    *reinterpret_cast<uint4*>(cp) = make_uint4(0u, 0u, 0u, 0u);
                    *reinterpret_cast<uint4*>(cp + 128) = make_uint4(0u, 0u, 0u, 0u);
                    __threadfence();
                    bar_sync(1, 256);
                }
                {
                    uint32_t* hp = &g_h[(lane >> 4) * 4][hkv][w * 128 + (2 * (r & 1) + (mi & 1)) * 32 + (((2 * (r >> 1) + (r7 >> 2)) ^ w) << 2) + t];
#pragma unroll
                    for (int d = 0; d < 4; d++) asm volatile("st.relaxed.gpu.global.u32 [%0], %1;" ::"l"(hp + d * 8 * 1024), "r"(hw) : "memory");
                }
                mbar_wait(bars + B_GO, 0);
                {
                    uint32_t* hp = &g_h[hkv][r][w * 128 + lane * 4];
                    uint4 v;
                    for (uint32_t it = 0;; it++) {
                        asm volatile("ld.relaxed.gpu.global.v4.u32 {%0,%1,%2,%3}, [%4];" : "=r"(v.x), "=r"(v.y), "=r"(v.z), "=r"(v.w) : "l"(hp) : "memory");
                        if (v.x != 0u && v.y != 0u && v.z != 0u && v.w != 0u) break;
                        if (it > kSpinLimit) __trap();
                    }
                    sts128(sb + SM_H + w * 512 + lane * 16, v.x, v.y, v.z, v.w);
                    *reinterpret_cast<uint4*>(hp) = make_uint4(0u, 0u, 0u, 0u);
                    __threadfence();
                }
                __syncwarp();
                if (lane == 0) mbar_arrive(bars + B_H);
#pragma unroll
                for (int i = 0; i < 16; i++) bf[i >> 2][i & 3] = 0u;
                static_assert(kWoN % kNSlot + 1 < kNSlot, "wo occupies two consecutive slots");
                abase += (kWoN % kNSlot) * kSlot;
                abar = bars + B_W + 8 * kg;
                PIN(abase); PIN(abar);
            }
            bar_sync(1, 256);
        }
    } else {
        TMCAL();
        int slot = 3, ph = 0;
        auto acquire = [&]() {
            mbar_wait(bars + B_FULL + 8 * slot, ph);
            return sb + SM_RING + slot * kSlot;
        };
        auto release = [&]() {
            __syncwarp();
            if (lane == 0) mbar_arrive_n(bars + B_EMPTY + 8 * slot, 2);
            if (++slot == kNSlot) { slot = 0; ph ^= 1; }
        };
        uint32_t koff[4];
#pragma unroll
        for (int c = 0; c < 4; c++)
            koff[c] = (w * 32 + r7 + 8 * (mi & 1)) * 128 + (((2 * c + (lane >> 4)) ^ r7) << 4);
        const uint32_t voff = (w >> 1) * 16384 + (r7 + 16 * (lane >> 4)) * 128 + (((4 * (w & 1) + (mi & 1)) ^ r7) << 4);
        const int ht = 2 * (t & 1) + (t >> 1);
        uint32_t* op = &g_o[0][hkv][((ht * 4 + w) * 8 + r) * 16 + (g & 3) * 4 + 2 * (g >> 2)];
        PINL(op);
        cluster_wait();
        uint32_t qf[8][2];
        mbar_wait_cl(bars + B_Q, 0);
#pragma unroll
        for (int ks = 0; ks < 8; ks++) {
            qf[ks][0] = lds32(sb + SM_Q + ((g & 3) * 64 + ks * 8 + t) * 4);
            qf[ks][1] = lds32(sb + SM_Q + ((g & 3) * 64 + ks * 8 + 4 + t) * 4);
        }
        TM(4);
        uint32_t mx2 = 0xff80ff80u;
        uint32_t mprev = 0xff80ff80u;
        float Mw = -INFINITY, l = 0.f, fin = 0.f;
        float O[4][4];
#pragma unroll
        for (int i = 0; i < 4; i++) { O[i][0] = O[i][1] = O[i][2] = O[i][3] = 0.f; }
#pragma unroll 1
        for (int c = 0; c < 4; c++) {
            uint32_t pa = sb + SM_P + (g & 3) * kPStride + (lane >> 4) * 16 + t * 4 + w * 64;
#pragma unroll 1
            for (int it = 0; it < 8; it++) {
                const uint32_t base = acquire();
                float sc[2][2][4];
#pragma unroll
                for (int i = 0; i < 16; i++) sc[i >> 3][(i >> 2) & 1][i & 3] = 0.f;
#pragma unroll
                for (int ks = 0; ks < 8; ks++) {
#pragma unroll
                    for (int mt = 0; mt < 2; mt++) {
                        uint32_t kf[4];
                        ldsm4(kf, base + (ks >> 2) * 16384 + mt * 2048 + koff[ks & 3]);
                        mma16816(sc[mt][ks & 1], kf, qf[ks][0], qf[ks][1]);
                    }
                }
                release();
#pragma unroll
                for (int mt = 0; mt < 2; mt++) {
                    const float c0 = t < 2 ? sc[mt][0][0] + sc[mt][1][0] : sc[mt][0][2] + sc[mt][1][2];
                    const float c1 = t < 2 ? sc[mt][0][1] + sc[mt][1][1] : sc[mt][0][3] + sc[mt][1][3];
                    const float scale = 0.08838834764831845f;
                    const uint32_t s2 = pack_bf16(c0, c1);
                    const uint32_t v = pack_bf16(bf_lo(s2) * scale, bf_hi(s2) * scale);
                    mx2 = max_bf16x2(mx2, v);
                    sts32(pa + mt * 32, movm(v));
                }
                pa += 256;
            }
            {
#pragma unroll
                for (int o = 2; o <= 16; o <<= 1) mx2 = max_bf16x2(mx2, __shfl_xor_sync(0xffffffffu, mx2, o));
                if (lane < 2) sts32(sb + SM_ML + lane * 16 + w * 4, mx2);
                bar_sync(2, 128);
                const uint4 a0 = lds128(sb + SM_ML), b0 = lds128(sb + SM_ML + 16);
                const uint32_t m01 = max_bf16x2(max_bf16x2(a0.x, a0.y), max_bf16x2(a0.z, a0.w));
                const uint32_t m23 = max_bf16x2(max_bf16x2(b0.x, b0.y), max_bf16x2(b0.z, b0.w));
                const uint32_t mw = (w & 2) ? m23 : m01, mt = (t & 1) ? m23 : m01;
                const float M = (w & 1) ? bf_hi(mw) : bf_lo(mw);
                l *= ex2((Mw - M) * kLog2e);
                Mw = M;
                const float al0 = ex2((bf_lo(mprev) - bf_lo(mt)) * kLog2e), al1 = ex2((bf_hi(mprev) - bf_hi(mt)) * kLog2e);
                mprev = mt;
#pragma unroll
                for (int i = 0; i < 4; i++) { O[i][0] *= al0; O[i][1] *= al1; O[i][2] *= al0; O[i][3] *= al1; }
                const uint32_t ea = sb + SM_P + w * kPStride + lane * 16;
#pragma unroll 2
                for (int i = 0; i < 4; i++) {
                    const uint4 sv = lds128(ea + i * 512);
                    const uint32_t uu[4] = {sv.x, sv.y, sv.z, sv.w};
                    uint32_t rr[4];
#pragma unroll
                    for (int e = 0; e < 4; e++) {
                        const float p0 = ex2((bf_lo(uu[e]) - M) * kLog2e), p1 = ex2((bf_hi(uu[e]) - M) * kLog2e);
                        l += p0 + p1;
                        rr[e] = pack_bf16(p0, p1);
                    }
                    sts128(ea + i * 512, rr[0], rr[1], rr[2], rr[3]);
                }
                float ls = l;
#pragma unroll
                for (int o = 16; o; o >>= 1) ls += __shfl_xor_sync(0xffffffffu, ls, o);
                if (lane == 0) stsf(sb + SM_ML + 64 + w * 4, ls);
                bar_sync(2, 128);
                fin = __fdividef(1.0f, __uint_as_float(lds32(sb + SM_ML + 64 + ht * 4)));
                PINF(fin);
                TM(5);
            }
            pa = sb + SM_P + (r7 & 3) * kPStride + (r7 >> 2) * 16 + mi * 32;
#pragma unroll 1
            for (int it = 0; it < 8; it++) {
                uint32_t pf[2][4];
                ldsm4(pf[0], pa);
                ldsm4(pf[1], pa + 128);
                pa += 256;
                const uint32_t base = acquire() + voff;
#pragma unroll
                for (int i = 0; i < 8; i++) {
#pragma unroll
                    for (int mt = 0; mt < 2; mt++) {
                        uint32_t vf[4];
                        ldsm4t(vf, (base ^ (mt * 32)) + (i >> 1) * 4096 + (i & 1) * 1024);
                        mma16816(O[2 * mt + (i & 1)], vf, pf[i >> 2][i & 2], pf[i >> 2][(i & 2) + 1]);
                    }
                }
                release();
            }
        }
        TM(6);
        uint32_t ow[2];
#pragma unroll
        for (int mt = 0; mt < 2; mt++) {
            const float (&A)[4] = O[2 * mt];
            const float (&B)[4] = O[2 * mt + 1];
            const float lo = (t < 2 ? A[0] : B[1]) + __shfl_xor_sync(0xffffffffu, t < 2 ? A[1] : B[0], 2);
            const float hi = (t < 2 ? A[2] : B[3]) + __shfl_xor_sync(0xffffffffu, t < 2 ? A[3] : B[2], 2);
            ow[mt] = encf(__uint_as_float(pack_bf16(lo * fin, hi * fin)));
        }
#pragma unroll
        for (int d = 0; d < 8; d++)
            asm volatile("st.relaxed.gpu.global.v2.u32 [%0], {%1,%2};" ::"l"(op + d * kHKV * 2048), "r"(ow[0]), "r"(ow[1]) : "memory");
        TM(7);
        {
            uint32_t hf[7][4];
            mbar_wait(bars + B_H, 0);
#pragma unroll
            for (int j = 0; j < 7; j++)
                ldsm4(hf[j], sb + SM_H + r7 * 512 + (2 * (j & 1) + (mi >> 1)) * 128 + (((2 * (j >> 1) + (mi & 1)) ^ r7) << 4));
            uint32_t wa2 = sb + SM_RING + (kW2N % kNSlot) * kSlot + (r7 + 8 * (mi >> 1)) * 128 + (((2 * w + (mi & 1)) ^ r7) << 4);
            uint32_t ya = mapa(sb + SM_G + r * 256 + (16 * w + g) * 4, 2 * t), yb = mapa(bars + B_Y, 2 * t), wbar = bars + B_W + 32;
            const uint32_t ostep = mapa(bars + B_Y, 2 * t + 1) - yb;
            PIN(wa2); PIN(ya); PIN(yb); PIN(wbar);
            {
                mbar_wait(wbar, 0);
                TM(13);
                float acc[4][4];
#pragma unroll
                for (int i = 0; i < 16; i++) acc[i >> 2][i & 3] = 0.f;
#pragma unroll
                for (int ks = 0; ks < 14; ks++) {
                    uint32_t af[4];
                    ldsm4t(af, wa2 + ks * 2048);
                    mma16816(acc[ks & 3], af, hf[ks >> 1][2 * (ks & 1)], hf[ks >> 1][2 * (ks & 1) + 1]);
                }
#pragma unroll
                for (int e = 0; e < 4; e++)
                    st_async(ya + (e & 1) * ostep + (e >> 1) * 32, __float_as_uint((acc[0][e] + acc[1][e]) + (acc[2][e] + acc[3][e])),
                             yb + (e & 1) * ostep);
                TM(12);
            }
        }
    }
    TMDUMP();
}

typedef CUresult (*EncodeFn)(CUtensorMap*, CUtensorMapDataType, cuuint32_t, void*, const cuuint64_t*, const cuuint64_t*,
                             const cuuint32_t*, const cuuint32_t*, CUtensorMapInterleave, CUtensorMapSwizzle,
                             CUtensorMapL2promotion, CUtensorMapFloatOOBfill);

void encode(EncodeFn fn, CUtensorMap* m, void* p, int rank, const cuuint64_t* dims, const cuuint64_t* strides,
            const cuuint32_t* box, int promo, CUtensorMapSwizzle sw = CU_TENSOR_MAP_SWIZZLE_128B) {
    const cuuint32_t es[4] = {1, 1, 1, 1};
    fn(m, CU_TENSOR_MAP_DATA_TYPE_BFLOAT16, rank, p, dims, strides, box, es, CU_TENSOR_MAP_INTERLEAVE_NONE,
       sw, (CUtensorMapL2promotion)promo, CU_TENSOR_MAP_FLOAT_OOB_FILL_NONE);
}

}

extern "C" void kernel_launch(void* const* d_in, const int* in_sizes, int n_in, void* d_out, int out_size) {
    (void)in_sizes; (void)n_in; (void)out_size;
    void* fnp = nullptr;
    cudaDriverEntryPointQueryResult qr;
    cudaGetDriverEntryPoint("cuTensorMapEncodeTiled", &fnp, cudaEnableDefault, &qr);
    EncodeFn fn = (EncodeFn)fnp;
    Maps maps;
    maps.p[0] = (const char*)d_in[1]; maps.p[1] = (const char*)d_in[2]; maps.p[2] = (const char*)d_in[3];
    maps.p[3] = (const char*)d_in[6]; maps.p[4] = (const char*)d_in[8]; maps.p[5] = (const char*)d_in[4];
    {
        const cuuint64_t dims[3] = {64, (cuuint64_t)kB * kHKV * kSK, 2}, str[2] = {256, 128};
        const cuuint32_t box[3] = {64, 128, 2};
        encode(fn, &maps.m[0], d_in[1], 3, dims, str, box, PR_KV);
        encode(fn, &maps.m[1], d_in[2], 3, dims, str, box, PR_KV);
    }
    {
        const cuuint64_t dims[3] = {4096, 512, 1}, str[2] = {8192, 8192 * 512};
        const cuuint32_t box[3] = {64, 256, 1};
        encode(fn, &maps.m[2], d_in[3], 3, dims, str, box, 3);
    }
    {
        const cuuint64_t dims[3] = {1792, 256, 2}, str[2] = {3584, 3584 * 256};
        const cuuint32_t box[3] = {32, 256, 2};
        encode(fn, &maps.m[3], d_in[6], 3, dims, str, box, 3, CU_TENSOR_MAP_SWIZZLE_64B);
    }
    {
        const cuuint64_t dims[3] = {512, 1792, 1}, str[2] = {1024, 1024 * 1792};
        const cuuint32_t box[3] = {64, 224, 1};
        encode(fn, &maps.m[4], d_in[8], 3, dims, str, box, 3);
    }
    {
        const cuuint64_t dims[4] = {512, 2, 8, 256}, str[3] = {8 * 1024, 1024, 16 * 1024};
        const cuuint32_t box[4] = {64, 2, 8, 8};
        encode(fn, &maps.m[5], d_in[4], 4, dims, str, box, 3);
    }
    cudaFuncSetAttribute(fused_decode_kernel, cudaFuncAttributeMaxDynamicSharedMemorySize, SM_BYTES);
    fused_decode_kernel<<<kGrid, kThreads, SM_BYTES>>>(
        (const __nv_bfloat16*)d_in[0], (const __nv_bfloat16*)d_in[7], (const __nv_bfloat16*)d_in[9],
        (__nv_bfloat16*)d_out, maps);
}
```

```cpp
#include <cuda_runtime.h>
#include <cuda_bf16.h>
#include <cuda.h>
#include <stdint.h>

namespace {

constexpr int kD = 512, kHKV = 8, kSK = 4096;
constexpr int kGrid = 64;
constexpr int kWarps = 14, kThreads = kWarps * 32;
constexpr int kSlot = 32768;
constexpr int kNSlot = 6;
constexpr int kItems = 70;
constexpr int kKVN = 3, kW2N = 67, kWoN = 68;
#define W_MAIN 4
#define LEAD 1
#define N_HEAD 6
#define HEAD_T0 900
#define HEAD_DT 550
#define SCHED_B 650
#define SCHED_E 43420
#define SCHED_D 325
#define SCHED_D2 240
#define OGATE_E 610
#define GO_N 40
constexpr int kWindow = W_MAIN, kWindowEnd = 3;
constexpr int kLead = LEAD;
constexpr int kGoN = GO_N;
constexpr int kHeadN = N_HEAD, kHeadT0 = HEAD_T0, kHeadDt = HEAD_DT;
constexpr int kGapW2 = SCHED_D, kGapWo = SCHED_D2, kGateO = OGATE_E - SCHED_D2;
constexpr double kItemNs = 625.6;
static_assert(kWindow >= 3 && kWindow < kNSlot && kNSlot <= 8 && kGoN < kKVN + 48, "ring");
static_assert(kWoN % kNSlot + 1 < kNSlot, "wo occupies two consecutive slots");

constexpr int kPStride = 2048 + 32;
constexpr int SM_RING = 0;
constexpr int SM_H = kNSlot * kSlot;
constexpr int SM_X = SM_H + 8 * 512;
constexpr int SM_P = SM_X + 8 * 1024;
constexpr int SM_SCR = SM_P + 4 * kPStride;
constexpr int SM_Q = SM_SCR + 4 * 2176;
constexpr int SM_Y = SM_Q + 1024;
constexpr int SM_S = SM_Y + 2048;
constexpr int SM_ML = SM_S + 2048;
constexpr int SM_B1 = SM_ML + 64;
constexpr int SM_PROG = SM_B1 + 64;
constexpr int SM_BAR = SM_PROG + 32;
constexpr int B_FULL = 0, B_EMPTY = 8 * kNSlot, B_WO = 16 * kNSlot, B_W2 = B_WO + 32, B_GO = B_W2 + 8, B_GO2 = B_GO + 8,
              B_X = B_GO2 + 8, B_Q = B_X + 8, B_Y = B_Q + 8, B_S = B_Y + 8, B_H = B_S + 8, B_END = B_H + 8;
constexpr int SM_BYTES = SM_BAR + B_END;
static_assert(SM_BYTES <= 232448, "smem");

constexpr float kLog2e = 1.4426950408889634f;
constexpr uint32_t kSpinLimit = 1u << 22;
constexpr long long kWaitCycles = 1ll << 32;

struct Params {
    CUtensorMap m[6];
    int sched_a, sched_b;
};

__device__ __align__(128) uint32_t g_o[8][kHKV][2048];
__device__ __align__(128) uint32_t g_h[8][8][1024];

__device__ __forceinline__ uint32_t smem_u32(const void* p) { return (uint32_t)__cvta_generic_to_shared(p); }
__device__ __forceinline__ void mbar_init(uint32_t bar, uint32_t cnt) {
    asm volatile("mbarrier.init.shared::cta.b64 [%0], %1;" ::"r"(bar), "r"(cnt) : "memory");
}
__device__ __forceinline__ void mbar_expect_tx(uint32_t bar, uint32_t bytes) {
    asm volatile("mbarrier.arrive.expect_tx.shared::cta.b64 _, [%0], %1;" ::"r"(bar), "r"(bytes) : "memory");
}
__device__ __forceinline__ void mbar_arrive(uint32_t bar) {
    asm volatile("mbarrier.arrive.shared::cta.b64 _, [%0];" ::"r"(bar) : "memory");
}
__device__ __forceinline__ void mbar_arrive_n(uint32_t bar, uint32_t n) {
    asm volatile("mbarrier.arrive.shared::cta.b64 _, [%0], %1;" ::"r"(bar), "r"(n) : "memory");
}
__device__ __forceinline__ bool mbar_try(uint32_t bar, uint32_t parity) {
    uint32_t ok;
    asm volatile("{\n.reg .pred p;\nmbarrier.try_wait.parity.relaxed.cluster.shared::cta.b64 p, [%1], %2;\nselp.u32 %0, 1, 0, p;\n}"
                 : "=r"(ok) : "r"(bar), "r"(parity) : "memory");
    return ok != 0u;
}
__device__ __forceinline__ bool mbar_try_cta(uint32_t bar, uint32_t parity) {
    uint32_t ok;
    asm volatile("{\n.reg .pred p;\nmbarrier.try_wait.parity.shared::cta.b64 p, [%1], %2;\nselp.u32 %0, 1, 0, p;\n}"
                 : "=r"(ok) : "r"(bar), "r"(parity) : "memory");
    return ok != 0u;
}
__device__ __forceinline__ bool mbar_test(uint32_t bar, uint32_t parity) {
    uint32_t ok;
    asm volatile("{\n.reg .pred p;\nmbarrier.test_wait.parity.shared::cta.b64 p, [%1], %2;\nselp.u32 %0, 1, 0, p;\n}"
                 : "=r"(ok) : "r"(bar), "r"(parity) : "memory");
    return ok != 0u;
}
__device__ __forceinline__ void mbar_wait(uint32_t bar, uint32_t parity) {
    if (mbar_try_cta(bar, parity)) return;
    const long long t0 = clock64();
    while (!mbar_try_cta(bar, parity))
        if (clock64() - t0 > kWaitCycles) __trap();
}
__device__ __forceinline__ void mbar_wait_cl(uint32_t bar, uint32_t parity) {
    if (!mbar_try(bar, parity)) {
        const long long t0 = clock64();
        while (!mbar_try(bar, parity))
            if (clock64() - t0 > kWaitCycles) __trap();
    }
    asm volatile("fence.acquire.sync_restrict::shared::cluster.cluster;" ::: "memory");
}
#define PIN(x) asm volatile("shfl.sync.bfly.b32 %0, %0, 0, 0x1f, 0xffffffff;" : "+r"(x) :: "memory")
#define PINF(x) asm volatile("" : "+f"(x) :: "memory")
#define PINL(x) asm volatile("{\n.reg .b32 lo, hi;\nmov.b64 {lo, hi}, %0;\nshfl.sync.bfly.b32 lo, lo, 0, 0x1f, 0xffffffff;\n" \
                             "shfl.sync.bfly.b32 hi, hi, 0, 0x1f, 0xffffffff;\nmov.b64 %0, {lo, hi};\n}" : "+l"(x) :: "memory")
__device__ __forceinline__ void tma4d(uint32_t dst, const CUtensorMap* m, int c0, int c1, int c2, int c3, uint32_t bar) {
    asm volatile("cp.async.bulk.tensor.4d.shared::cluster.global.mbarrier::complete_tx::bytes [%0], [%1, {%3, %4, %5, %6}], [%2];"
                 ::"r"(dst), "l"(m), "r"(bar), "r"(c0), "r"(c1), "r"(c2), "r"(c3) : "memory");
}
__device__ __forceinline__ void tma3d(uint32_t dst, const CUtensorMap* m, int c0, int c1, int c2, uint32_t bar) {
    asm volatile("cp.async.bulk.tensor.3d.shared::cluster.global.mbarrier::complete_tx::bytes [%0], [%1, {%3, %4, %5}], [%2];"
                 ::"r"(dst), "l"(m), "r"(bar), "r"(c0), "r"(c1), "r"(c2) : "memory");
}
__device__ __forceinline__ void tma3d_hint(uint32_t dst, const CUtensorMap* m, int c0, int c1, int c2, uint32_t bar, uint64_t pol) {
    asm volatile("cp.async.bulk.tensor.3d.shared::cluster.global.mbarrier::complete_tx::bytes.L2::cache_hint [%0], [%1, {%3, %4, %5}], [%2], %6;"
                 ::"r"(dst), "l"(m), "r"(bar), "r"(c0), "r"(c1), "r"(c2), "l"(pol) : "memory");
}
__device__ __forceinline__ void bar_sync(int id, int n) { asm volatile("barrier.sync %0, %1;" ::"r"(id), "r"(n) : "memory"); }
__device__ __forceinline__ bool elect_one() {
    uint32_t p;
    asm volatile("{\n.reg .pred p;\nelect.sync _|p, 0xffffffff;\nselp.u32 %0, 1, 0, p;\n}" : "=r"(p));
    return p != 0u;
}
__device__ __forceinline__ void cluster_arrive() { asm volatile("barrier.cluster.arrive.relaxed;" ::: "memory"); }
__device__ __forceinline__ void cluster_wait() { asm volatile("barrier.cluster.wait;" ::: "memory"); }
__device__ __forceinline__ uint32_t mapa(uint32_t a, uint32_t rank) {
    uint32_t d;
    asm("mapa.shared::cluster.u32 %0, %1, %2;" : "=r"(d) : "r"(a), "r"(rank));
    return d;
}
__device__ __forceinline__ void st_async(uint32_t a, uint32_t v, uint32_t bar) {
    asm volatile("st.async.shared::cluster.mbarrier::complete_tx::bytes.u32 [%0], %1, [%2];" ::"r"(a), "r"(v), "r"(bar) : "memory");
}
__device__ __forceinline__ void st_async2_pred(uint32_t a, float x, float y, uint32_t bar, bool c) {
    asm volatile("{\n.reg .pred p;\nsetp.ne.u32 p, %4, 0;\n@p st.async.shared::cluster.mbarrier::complete_tx::bytes.v2.f32 [%0], {%1,%2}, [%3];\n}"
                 ::"r"(a), "f"(x), "f"(y), "r"(bar), "r"((uint32_t)c) : "memory");
}
__device__ __forceinline__ void st_async4(uint32_t a, uint32_t x, uint32_t y, uint32_t z, uint32_t w, uint32_t bar) {
    asm volatile("st.async.shared::cluster.mbarrier::complete_tx::bytes.v4.u32 [%0], {%1,%2,%3,%4}, [%5];"
                 ::"r"(a), "r"(x), "r"(y), "r"(z), "r"(w), "r"(bar) : "memory");
}

__device__ __forceinline__ void ldsm4(uint32_t (&r)[4], uint32_t a) {
    asm volatile("ldmatrix.sync.aligned.m8n8.x4.shared.b16 {%0,%1,%2,%3}, [%4];"
                 : "=r"(r[0]), "=r"(r[1]), "=r"(r[2]), "=r"(r[3]) : "r"(a) : "memory");
}
__device__ __forceinline__ void ldsm4t(uint32_t (&r)[4], uint32_t a) {
    asm volatile("ldmatrix.sync.aligned.m8n8.x4.trans.shared.b16 {%0,%1,%2,%3}, [%4];"
                 : "=r"(r[0]), "=r"(r[1]), "=r"(r[2]), "=r"(r[3]) : "r"(a) : "memory");
}
__device__ __forceinline__ void mma16816(float (&c)[4], const uint32_t (&a)[4], uint32_t b0, uint32_t b1) {
    asm volatile("mma.sync.aligned.m16n8k16.row.col.f32.bf16.bf16.f32 {%0,%1,%2,%3}, {%4,%5,%6,%7}, {%8,%9}, {%0,%1,%2,%3};"
                 : "+f"(c[0]), "+f"(c[1]), "+f"(c[2]), "+f"(c[3])
                 : "r"(a[0]), "r"(a[1]), "r"(a[2]), "r"(a[3]), "r"(b0), "r"(b1));
}
__device__ __forceinline__ uint32_t movm(uint32_t a) {
    uint32_t d;
    asm volatile("movmatrix.sync.aligned.m8n8.trans.b16 %0, %1;" : "=r"(d) : "r"(a));
    return d;
}
__device__ __forceinline__ uint32_t pack_bf16(float lo, float hi) {
    uint32_t d;
    asm("cvt.rn.bf16x2.f32 %0, %1, %2;" : "=r"(d) : "f"(hi), "f"(lo));
    return d;
}
__device__ __forceinline__ float bf_lo(uint32_t u) { return __uint_as_float(u << 16); }
__device__ __forceinline__ float bf_hi(uint32_t u) { return __uint_as_float(u & 0xffff0000u); }
__device__ __forceinline__ float bfr(float v) { return __uint_as_float(pack_bf16(0.f, v)); }
__device__ __forceinline__ uint32_t max_bf16x2(uint32_t a, uint32_t b) {
    uint32_t d;
    asm("max.bf16x2 %0, %1, %2;" : "=r"(d) : "r"(a), "r"(b));
    return d;
}
__device__ __forceinline__ float ex2(float x) {
    float y;
    asm("ex2.approx.ftz.f32 %0, %1;" : "=f"(y) : "f"(x));
    return y;
}
__device__ __forceinline__ float mul_sigmoid(float v, float z) { return __fdividef(v, 1.0f + ex2(fminf(-kLog2e * z, 120.f))); }
__device__ __forceinline__ uint32_t lds32(uint32_t a) { uint32_t v; asm volatile("ld.shared.u32 %0, [%1];" : "=r"(v) : "r"(a) : "memory"); return v; }
__device__ __forceinline__ float2 ldsf2(uint32_t a) { float2 v; asm volatile("ld.shared.v2.f32 {%0,%1}, [%2];" : "=f"(v.x), "=f"(v.y) : "r"(a) : "memory"); return v; }
__device__ __forceinline__ uint4 lds128(uint32_t a) {
    uint4 v;
    asm volatile("ld.shared.v4.u32 {%0,%1,%2,%3}, [%4];" : "=r"(v.x), "=r"(v.y), "=r"(v.z), "=r"(v.w) : "r"(a) : "memory");
    return v;
}
__device__ __forceinline__ void sts32(uint32_t a, uint32_t v) { asm volatile("st.shared.u32 [%0], %1;" ::"r"(a), "r"(v) : "memory"); }
__device__ __forceinline__ void stsf(uint32_t a, float v) { asm volatile("st.shared.f32 [%0], %1;" ::"r"(a), "f"(v) : "memory"); }
__device__ __forceinline__ void sts128(uint32_t a, uint32_t x, uint32_t y, uint32_t z, uint32_t w) {
    asm volatile("st.shared.v4.u32 [%0], {%1,%2,%3,%4};" ::"r"(a), "r"(x), "r"(y), "r"(z), "r"(w) : "memory");
}
__device__ __forceinline__ uint32_t enc(uint32_t b) { return b == 0u ? 0x80000000u : b; }
__device__ __forceinline__ void st_pred32(void* p, uint32_t v, bool c) {
    asm volatile("{\n.reg .pred p;\nsetp.ne.u32 p, %2, 0;\n@p st.global.u32 [%0], %1;\n}" ::"l"(p), "r"(v), "r"((uint32_t)c) : "memory");
}
__device__ __forceinline__ void ld_rlx4_pred(uint32_t (&v)[4], const uint32_t* p, bool c) {
    asm volatile("{\n.reg .pred p;\nsetp.ne.u32 p, %5, 0;\n@p ld.relaxed.gpu.global.v4.u32 {%0,%1,%2,%3}, [%4];\n}"
                 : "+r"(v[0]), "+r"(v[1]), "+r"(v[2]), "+r"(v[3]) : "l"(p), "r"((uint32_t)c) : "memory");
}
__device__ __forceinline__ uint32_t gt32() { uint32_t c; asm volatile("mov.u32 %0, %globaltimer_lo;" : "=r"(c) :: "memory"); return c; }
__device__ __forceinline__ void wait_until(uint32_t t0, int ns) {
    while (gt32() - t0 < (uint32_t)max(ns, 0)) {}
}
__device__ __forceinline__ uint32_t ldg32(const void* p) {
    uint32_t v;
    asm volatile("ld.global.nc.u32 %0, [%1];" : "=r"(v) : "l"(p));
    return v;
}

__global__ void __cluster_dims__(8, 1, 1) __launch_bounds__(kThreads, 1)
fused_decode_kernel(const __nv_bfloat16* __restrict__ x, const __nv_bfloat16* __restrict__ b1,
                    const __nv_bfloat16* __restrict__ b2, __nv_bfloat16* __restrict__ out,
                    const __grid_constant__ Params prm) {
    extern __shared__ __align__(1024) unsigned char smem_raw[];
    const uint32_t sb = smem_u32(smem_raw);
    const uint32_t bars = sb + SM_BAR;
    const int tid = threadIdx.x, wid = tid >> 5, lane = tid & 31;
    const int hkv = blockIdx.x >> 3, r = blockIdx.x & 7;
    if (tid < 32) {
        if (elect_one()) {
            mbar_init(bars + B_FULL, 1);
            mbar_init(bars + B_FULL + 8, 1);
            asm volatile("fence.mbarrier_init.release.cluster;" ::: "memory");
#pragma unroll
            for (int n = 0; n < 2; n++) {
                mbar_expect_tx(bars + B_FULL + 8 * n, kSlot);
                tma3d(sb + SM_RING + n * kSlot, &prm.m[2], blockIdx.x * 64, n * 256, 0, bars + B_FULL + 8 * n);
            }
#pragma unroll
            for (int n = 2; n < kNSlot; n++) mbar_init(bars + B_FULL + 8 * n, 1);
            asm volatile("fence.mbarrier_init.release.cluster;" ::: "memory");
            mbar_expect_tx(bars + B_FULL + 16, r < 7 ? kSlot : 0);
            if (r < 7) tma3d(sb + SM_RING + 2 * kSlot, &prm.m[3], hkv * 224 + r * 32, 0, 0, bars + B_FULL + 16);
        }
    }
    const uint32_t t_start = gt32();
    if (wid == 1) asm volatile("prefetch.global.L1 [%0];" ::"l"(x + r * kD + lane * 16) : "memory");
    if (wid == 3 && lane < 4) asm volatile("prefetch.tensormap [%0];" ::"l"(&prm.m[lane + (lane & 2)]) : "memory");
    if (tid == 64) {
        if (sb & 1023u) __trap();
#pragma unroll
        for (int n = 0; n < kNSlot; n++) mbar_init(bars + B_EMPTY + 8 * n, 8);
#pragma unroll
        for (int n = B_WO; n < B_END; n += 8) mbar_init(bars + n, n < B_H ? 1 : 8);
        asm volatile("fence.mbarrier_init.release.cluster;" ::: "memory");
        sts128(sb + SM_PROG, 0, 0, 0, 0);
        sts128(sb + SM_PROG + 16, 0, 0, 0, 0);
        asm volatile("fence.release.sync_restrict::shared::cta.cluster;" ::: "memory");
        mbar_expect_tx(bars + B_X, 8192);
        mbar_expect_tx(bars + B_Q, 1024);
        mbar_expect_tx(bars + B_Y, 2048);
        mbar_expect_tx(bars + B_S, 2048);
    }
    __syncwarp();
    cluster_arrive();
    const int w = (wid - 2) & 7;
    const int g = lane >> 2, t = lane & 3, r7 = lane & 7, mi = lane >> 3;

    if (wid == 1) {
        {
            const uint4* xr = reinterpret_cast<const uint4*>(x + r * kD) + lane;
            const uint4 xv0 = __ldg(xr), xv1 = __ldg(xr + 32);
            float f[16];
            const uint32_t u[8] = {xv0.x, xv0.y, xv0.z, xv0.w, xv1.x, xv1.y, xv1.z, xv1.w};
#pragma unroll
            for (int i = 0; i < 8; i++) { f[2 * i] = bf_lo(u[i]); f[2 * i + 1] = bf_hi(u[i]); }
            float s = 0.f;
#pragma unroll
            for (int i = 0; i < 16; i++) s += f[i];
#pragma unroll
            for (int o = 16; o; o >>= 1) s += __shfl_xor_sync(0xffffffffu, s, o);
            const float mean = s * (1.0f / kD);
            float vs = 0.f;
#pragma unroll
            for (int i = 0; i < 16; i++) { const float d = f[i] - mean; vs = fmaf(d, d, vs); }
#pragma unroll
            for (int o = 16; o; o >>= 1) vs += __shfl_xor_sync(0xffffffffu, vs, o);
            const float mb = bfr(mean);
            const float den = bfr(__fsqrt_rn(bfr(bfr(vs * (1.0f / kD)) + 1e-5f)));
            const float rden = __frcp_rn(den);
            uint32_t q[8];
#pragma unroll
            for (int i = 0; i < 8; i++) {
                const uint32_t d2 = pack_bf16(f[2 * i] - mb, f[2 * i + 1] - mb);
                q[i] = pack_bf16(bf_lo(d2) * rden, bf_hi(d2) * rden);
            }
            const uint32_t xoff = SM_X + r * 1024 + ((lane >> 1) & 7) * 128 + (((2 * (lane >> 4) + (lane & 1)) ^ r) << 4);
            cluster_wait();
#pragma unroll 1
            for (int d = 0; d < 8; d++) {
                const uint32_t rb = mapa(sb, d), xa = rb + xoff;
                st_async4(xa, q[0], q[1], q[2], q[3], rb + SM_BAR + B_X);
                st_async4(xa ^ 64, q[4], q[5], q[6], q[7], rb + SM_BAR + B_X);
            }
        }
        const int col = hkv * 64 + 2 * lane;
        const uint32_t xw = ldg32(x + r * kD + col), bw = ldg32(b2 + col);
        __nv_bfloat16* dst = out + r * kD + col;
        uint32_t pa = sb + SM_Y + lane * 8, pbar = bars + B_Y;
        PINL(dst);
        float g0 = 0.f, g1 = 0.f;
#pragma unroll 1
        for (int pass = 0; pass < 2; pass++) {
            mbar_wait_cl(pbar, 0);
            float2 v[8];
#pragma unroll
            for (int c = 0; c < 8; c++) v[c] = ldsf2(pa + c * 256);
            const uint32_t sw = pack_bf16(((v[0].x + v[1].x) + (v[2].x + v[3].x)) + ((v[4].x + v[5].x) + (v[6].x + v[7].x)),
                                          ((v[0].y + v[1].y) + (v[2].y + v[3].y)) + ((v[4].y + v[5].y) + (v[6].y + v[7].y)));
            const uint32_t pw = pack_bf16(bf_lo(sw) * g0, bf_hi(sw) * g1);
            st_pred32(dst, pack_bf16(bf_lo(xw) + bf_lo(pw), bf_hi(xw) + bf_hi(pw)), pass);
            if (pass) break;
            const uint32_t yw = pack_bf16(bf_lo(sw) + bf_lo(bw), bf_hi(sw) + bf_hi(bw));
            const uint32_t gw = pack_bf16(mul_sigmoid(bf_lo(yw), bf_lo(yw)), mul_sigmoid(bf_hi(yw), bf_hi(yw)));
            g0 = bf_lo(gw);
            g1 = bf_hi(gw);
            pa = sb + SM_S + lane * 8;
            pbar = bars + B_S;
        }
    } else if (wid == 0) {
        cluster_wait();
        const int kvrow0 = (r * kHKV + hkv) * kSK;
        const uint32_t prog_remote = mapa(sb + SM_PROG + r * 4, lane & 7);
        uint64_t stream_pol;
        asm volatile("createpolicy.fractional.L2::evict_first.b64 %0, 1.0;" : "=l"(stream_pol));
        int slot = kKVN, ph = 0;
        int landed = 0, lslot = 0, lph = 0;
#pragma unroll 1
        for (int n = kKVN; n < kItems; n++) {
            if (n >= kNSlot) mbar_wait(bars + B_EMPTY + 8 * slot, ph ^ 1);
            for (const int need = n - (n >= kW2N ? kWindowEnd : kWindow); landed <= need; landed++) {
                mbar_wait(bars + B_FULL + 8 * lslot, lph);
                if (++lslot == kNSlot) { lslot = 0; lph ^= 1; }
            }
            wait_until(t_start, n < kHeadN ? kHeadT0 + (n - kKVN) * kHeadDt
                                           : prm.sched_a + n * prm.sched_b + (n < kW2N ? 0 : n < kWoN ? kGapW2 : kGapWo));
            if (n < kW2N) {
                if (lane < 8) asm volatile("st.relaxed.cluster.shared::cluster.u32 [%0], %1;" ::"r"(prog_remote), "r"(n) : "memory");
                for (uint32_t it = 0;; it++) {
                    int p;
                    asm volatile("ld.relaxed.cluster.shared::cta.u32 %0, [%1];" : "=r"(p) : "r"(sb + SM_PROG + (lane & 7) * 4) : "memory");
                    if (__all_sync(0xffffffffu, max(p, kKVN) + kLead >= n)) break;
                    if (it > kSpinLimit * 16) __trap();
                }
            }
            if (elect_one()) {
                const uint32_t dst = sb + SM_RING + slot * kSlot;
                if (n < kW2N) {
                    const int u = n - kKVN;
                    mbar_expect_tx(bars + B_FULL + 8 * slot, kSlot);
                    tma3d_hint(dst, &prm.m[(u >> 3) & 1], 0, kvrow0 + (u >> 4) * 1024 + (u & 7) * 128, 0, bars + B_FULL + 8 * slot, stream_pol);
                } else if (n >= kWoN) {
                    const uint32_t wb = bars + B_WO + 16 * (n - kWoN);
                    mbar_expect_tx(wb, kSlot / 2);
                    tma4d(dst, &prm.m[5], hkv * 64, 0, 0, r * 32 + (n - kWoN) * 16, wb);
                    mbar_expect_tx(wb + 8, kSlot / 2);
                    tma4d(dst + kSlot / 2, &prm.m[5], hkv * 64, 0, 0, r * 32 + (n - kWoN) * 16 + 8, wb + 8);
                } else {
                    mbar_expect_tx(bars + B_W2, 224 * 128);
                    tma3d(dst, &prm.m[4], hkv * 64, r * 224, 0, bars + B_W2);
                }
                if (n == kGoN) mbar_arrive(bars + B_GO);
            }
            __syncwarp();
            if (++slot == kNSlot) { slot = 0; ph ^= 1; }
        }
        wait_until(gt32(), kGateO);
        mbar_wait(bars + B_W2, 0);
        if (lane == 0) mbar_arrive(bars + B_GO2);
    } else if (wid < 10) {
        const int kg = w >> 1, ch = w & 1;
        if (w == 7 && lane < 16) sts32(sb + SM_B1 + lane * 4, ldg32(b1 + hkv * 224 + (r < 7 ? r : 0) * 32 + 2 * lane));
        uint32_t wa = sb + SM_SCR + kg * 2176 + t * 544 + (ch * 32 + g) * 4;
        uint32_t ra = sb + SM_SCR + w * 272 + lane * 8;
        uint32_t* op = &g_o[hkv][r][kg * 512 + lane * 4];
        const uint32_t baddr = sb + SM_X + r7 * 1024 + (mi & 1) * 128 + (((2 * kg + (mi >> 1)) ^ r7) << 4);
        uint32_t abase = sb + SM_RING + kg * (kSlot / 2) + (r7 + 16 * (mi >> 1)) * 128 + (((4 * ch + (mi & 1)) ^ r7) << 4);
        uint32_t abar = bars + B_FULL + 8 * (kg >> 1);
        uint32_t sa = mapa(sb + SM_S + r * 256 + lane * 8, w), sbar = mapa(bars + B_S, w);
        PIN(wa); PIN(ra); PINL(op); PIN(sa); PIN(sbar);
        uint32_t bf[4][4];
        auto fetch_o = [&]() {
            bool all = true;
#pragma unroll
            for (int j = 0; j < 4; j++) {
                const bool ok = bf[j][0] != 0u && bf[j][1] != 0u && bf[j][2] != 0u && bf[j][3] != 0u;
                all = all && ok;
                ld_rlx4_pred(bf[j], op + j * 128, !ok);
            }
            return __all_sync(0xffffffffu, all);
        };
        cluster_wait();
        mbar_wait_cl(bars + B_X, 0);
#pragma unroll 1
        for (int pass = 0; pass < 3; pass++) {
            float acc[2][2][4];
#pragma unroll
            for (int i = 0; i < 16; i++) acc[i >> 3][(i >> 2) & 1][i & 3] = 0.f;
            bool stream = true;
            if (pass == 2) {
                mbar_wait(bars + B_GO2, 0);
                for (uint32_t it = 0;; it++) {
                    stream = fetch_o();
                    if (stream || kg < 2 || __all_sync(0xffffffffu, mbar_test(abar, 0))) break;
                    if (it > kSpinLimit) __trap();
                }
            } else {
#pragma unroll
                for (int i = 0; i < 4; i++) ldsm4(bf[i], baddr + ((i * 256 + (pass & ch) * 512) & 1023));
            }
            if (pass == 1) {
                const uint32_t a1 = sb + SM_RING + 2 * kSlot + w * 4096 + (r7 + 16 * (mi >> 1)) * 64 + (((mi & 1) ^ (r7 >> 1)) << 4);
                mbar_wait(bars + B_FULL + 16, 0);
#pragma unroll
                for (int ks = 0; ks < 4; ks++) {
#pragma unroll
                    for (int mt = 0; mt < 2; mt++) {
                        uint32_t af[4];
                        ldsm4t(af, (a1 ^ (mt * 32)) + (ks >> 1) * 2048 + (ks & 1) * 512);
                        mma16816(acc[mt][ks & 1], af, bf[ks >> 1][2 * (ks & 1)], bf[ks >> 1][2 * (ks & 1) + 1]);
                    }
                }
            } else if (stream) {
                mbar_wait(abar, 0);
#pragma unroll
                for (int ks = 0; ks < 8; ks++) {
#pragma unroll
                    for (int mt = 0; mt < 2; mt++) {
                        uint32_t af[4];
                        ldsm4t(af, (abase ^ (mt * 32)) + (ks >> 1) * 4096 + (ks & 1) * 1024);
                        mma16816(acc[mt][ks & 1], af, bf[ks >> 1][2 * (ks & 1)], bf[ks >> 1][2 * (ks & 1) + 1]);
                    }
                }
            } else {
                uint32_t af[8][2][4];
                mbar_wait(abar, 0);
#pragma unroll
                for (int ks = 0; ks < 8; ks++) {
                    ldsm4t(af[ks][0], abase + (ks >> 1) * 4096 + (ks & 1) * 1024);
                    ldsm4t(af[ks][1], (abase ^ 32) + (ks >> 1) * 4096 + (ks & 1) * 1024);
                }
                for (uint32_t it = 0; !fetch_o(); it++)
                    if (it > kSpinLimit) __trap();
#pragma unroll
                for (int ks = 0; ks < 8; ks++) {
                    mma16816(acc[0][ks & 1], af[ks][0], bf[ks >> 1][2 * (ks & 1)], bf[ks >> 1][2 * (ks & 1) + 1]);
                    mma16816(acc[1][ks & 1], af[ks][1], bf[ks >> 1][2 * (ks & 1)], bf[ks >> 1][2 * (ks & 1) + 1]);
                }
            }
#pragma unroll
            for (int mt = 0; mt < 2; mt++) {
#pragma unroll
                for (int e = 0; e < 4; e++)
                    stsf(wa + (e & 1) * 272 + (mt * 16 + 8 * (e >> 1)) * 4, acc[mt][0][e] + acc[mt][1][e]);
            }
            bar_sync(1, 256);
            const float2 p0 = ldsf2(ra), p1 = ldsf2(ra + 2176), p2 = ldsf2(ra + 2 * 2176), p3 = ldsf2(ra + 3 * 2176);
            float s0 = (p0.x + p1.x) + (p2.x + p3.x), s1 = (p0.y + p1.y) + (p2.y + p3.y);
            st_async2_pred(sa, s0, s1, sbar, pass == 2);
            if (pass == 2) break;
            if (pass == 0) {
                const uint32_t rb = mapa(sb, w);
                st_async(rb + SM_Q + (r * 32 + lane) * 4, pack_bf16(s0, s1), rb + SM_BAR + B_Q);
                if (lane == 0) mbar_arrive_n(bars + B_EMPTY + 8 * (kg >> 1), 2);
            } else {
                if (lane == 0) mbar_arrive(bars + B_EMPTY + 16);
                s0 += __shfl_xor_sync(0xffffffffu, s0, 16);
                s1 += __shfl_xor_sync(0xffffffffu, s1, 16);
                const uint32_t sw = pack_bf16(s0, s1), b1w = lds32(sb + SM_B1 + (lane & 15) * 4);
                const uint32_t vw = pack_bf16(bf_lo(sw) + bf_lo(b1w), bf_hi(sw) + bf_hi(b1w));
                const float v0 = bf_lo(vw), v1 = bf_hi(vw);
                const float c = 2.0f * 0.7978845608028654f;
                uint32_t hw = pack_bf16(mul_sigmoid(v0, c * (v0 + 0.044715f * v0 * v0 * v0)),
                                        mul_sigmoid(v1, c * (v1 + 0.044715f * v1 * v1 * v1)));
                hw = r < 7 ? enc(hw) : 0x80000000u;
                {
                    uint32_t* cp = &g_o[w][hkv][(g * 16 + r) * 16 + t * 4];
                    *reinterpret_cast<uint4*>(cp) = make_uint4(0u, 0u, 0u, 0u);
                    *reinterpret_cast<uint4*>(cp + 128) = make_uint4(0u, 0u, 0u, 0u);
                    __threadfence();
                    bar_sync(1, 256);
                }
                {
                    uint32_t* hp = &g_h[(lane >> 4) * 4][hkv][w * 128 + (2 * (r & 1) + (mi & 1)) * 32 + (((2 * (r >> 1) + (r7 >> 2)) ^ w) << 2) + t];
#pragma unroll
                    for (int d = 0; d < 4; d++) asm volatile("st.relaxed.gpu.global.u32 [%0], %1;" ::"l"(hp + d * 8 * 1024), "r"(hw) : "memory");
                }
                mbar_wait(bars + B_GO, 0);
                {
                    uint32_t* hp = &g_h[hkv][r][w * 128 + lane * 4];
                    uint4 v;
                    for (uint32_t it = 0;; it++) {
                        asm volatile("ld.relaxed.gpu.global.v4.u32 {%0,%1,%2,%3}, [%4];" : "=r"(v.x), "=r"(v.y), "=r"(v.z), "=r"(v.w) : "l"(hp) : "memory");
                        if (v.x != 0u && v.y != 0u && v.z != 0u && v.w != 0u) break;
                        if (it > kSpinLimit) __trap();
                    }
                    sts128(sb + SM_H + w * 512 + lane * 16, v.x, v.y, v.z, v.w);
                    *reinterpret_cast<uint4*>(hp) = make_uint4(0u, 0u, 0u, 0u);
                    __threadfence();
                }
                __syncwarp();
                if (lane == 0) mbar_arrive(bars + B_H);
#pragma unroll
                for (int i = 0; i < 16; i++) bf[i >> 2][i & 3] = 0u;
                abase += (kWoN % kNSlot) * kSlot;
                abar = bars + B_WO + 8 * kg;
                PIN(abase); PIN(abar);
            }
            bar_sync(1, 256);
        }
    } else {
        int slot = kKVN, ph = 0;
        auto acquire = [&]() {
            mbar_wait(bars + B_FULL + 8 * slot, ph);
            return sb + SM_RING + slot * kSlot;
        };
        auto release = [&]() {
            __syncwarp();
            if (lane == 0) mbar_arrive_n(bars + B_EMPTY + 8 * slot, 2);
            if (++slot == kNSlot) { slot = 0; ph ^= 1; }
        };
        uint32_t koff[4];
#pragma unroll
        for (int c = 0; c < 4; c++)
            koff[c] = (w * 32 + r7 + 8 * (mi & 1)) * 128 + (((2 * c + (lane >> 4)) ^ r7) << 4);
        const uint32_t voff = (w >> 1) * 16384 + (r7 + 16 * (lane >> 4)) * 128 + (((4 * (w & 1) + (mi & 1)) ^ r7) << 4);
        const int ht = 2 * (t & 1) + (t >> 1);
        uint32_t* op = &g_o[0][hkv][((ht * 4 + w) * 8 + r) * 16 + (g & 3) * 4 + 2 * (g >> 2)];
        PINL(op);
        cluster_wait();
        uint32_t qf[8][2];
        mbar_wait_cl(bars + B_Q, 0);
#pragma unroll
        for (int ks = 0; ks < 8; ks++) {
            qf[ks][0] = lds32(sb + SM_Q + ((g & 3) * 64 + ks * 8 + t) * 4);
            qf[ks][1] = lds32(sb + SM_Q + ((g & 3) * 64 + ks * 8 + 4 + t) * 4);
        }
        uint32_t mx2 = 0xff7fff7fu;
        uint32_t mprev = 0xff7fff7fu;
        float Mw = bf_hi(mprev), l = 0.f, fin = 0.f;
        float O[4][4];
#pragma unroll
        for (int i = 0; i < 4; i++) { O[i][0] = O[i][1] = O[i][2] = O[i][3] = 0.f; }
#pragma unroll 1
        for (int c = 0; c < 4; c++) {
            uint32_t pa = sb + SM_P + (g & 3) * kPStride + (lane >> 4) * 16 + t * 4 + w * 64;
#pragma unroll 1
            for (int it = 0; it < 8; it++) {
                const uint32_t base = acquire();
                float sc[2][2][4];
#pragma unroll
                for (int i = 0; i < 16; i++) sc[i >> 3][(i >> 2) & 1][i & 3] = 0.f;
#pragma unroll
                for (int ks = 0; ks < 8; ks++) {
#pragma unroll
                    for (int mt = 0; mt < 2; mt++) {
                        uint32_t kf[4];
                        ldsm4(kf, base + (ks >> 2) * 16384 + mt * 2048 + koff[ks & 3]);
                        mma16816(sc[mt][ks & 1], kf, qf[ks][0], qf[ks][1]);
                    }
                }
                release();
#pragma unroll
                for (int mt = 0; mt < 2; mt++) {
                    const float c0 = t < 2 ? sc[mt][0][0] + sc[mt][1][0] : sc[mt][0][2] + sc[mt][1][2];
                    const float c1 = t < 2 ? sc[mt][0][1] + sc[mt][1][1] : sc[mt][0][3] + sc[mt][1][3];
                    const float scale = 0.08838834764831845f;
                    const uint32_t s2 = pack_bf16(c0, c1);
                    const uint32_t v = pack_bf16(bf_lo(s2) * scale, bf_hi(s2) * scale);
                    mx2 = max_bf16x2(mx2, v);
                    sts32(pa + mt * 32, movm(v));
                }
                pa += 256;
            }
            {
#pragma unroll
                for (int o = 2; o <= 16; o <<= 1) mx2 = max_bf16x2(mx2, __shfl_xor_sync(0xffffffffu, mx2, o));
                if (lane < 2) sts32(sb + SM_ML + lane * 16 + w * 4, mx2);
                bar_sync(2, 128);
                const uint4 a0 = lds128(sb + SM_ML), b0 = lds128(sb + SM_ML + 16);
                const uint32_t m01 = max_bf16x2(max_bf16x2(a0.x, a0.y), max_bf16x2(a0.z, a0.w));
                const uint32_t m23 = max_bf16x2(max_bf16x2(b0.x, b0.y), max_bf16x2(b0.z, b0.w));
                const uint32_t mw = (w & 2) ? m23 : m01, mt = (t & 1) ? m23 : m01;
                const float M = (w & 1) ? bf_hi(mw) : bf_lo(mw);
                l *= ex2((Mw - M) * kLog2e);
                Mw = M;
                const float al0 = ex2((bf_lo(mprev) - bf_lo(mt)) * kLog2e), al1 = ex2((bf_hi(mprev) - bf_hi(mt)) * kLog2e);
                mprev = mt;
#pragma unroll
                for (int i = 0; i < 4; i++) { O[i][0] *= al0; O[i][1] *= al1; O[i][2] *= al0; O[i][3] *= al1; }
                const uint32_t ea = sb + SM_P + w * kPStride + lane * 16;
#pragma unroll 2
                for (int i = 0; i < 4; i++) {
                    const uint4 sv = lds128(ea + i * 512);
                    const uint32_t uu[4] = {sv.x, sv.y, sv.z, sv.w};
                    uint32_t rr[4];
#pragma unroll
                    for (int e = 0; e < 4; e++) {
                        const float p0 = ex2((bf_lo(uu[e]) - M) * kLog2e), p1 = ex2((bf_hi(uu[e]) - M) * kLog2e);
                        l += p0 + p1;
                        rr[e] = pack_bf16(p0, p1);
                    }
                    sts128(ea + i * 512, rr[0], rr[1], rr[2], rr[3]);
                }
                float ls = l;
#pragma unroll
                for (int o = 16; o; o >>= 1) ls += __shfl_xor_sync(0xffffffffu, ls, o);
                if (lane == 0) stsf(sb + SM_ML + 32 + w * 4, ls);
                bar_sync(2, 128);
                fin = __fdividef(1.0f, __uint_as_float(lds32(sb + SM_ML + 32 + ht * 4)));
                PINF(fin);
                if (c == 3) mbar_wait(bars + B_H, 0);
            }
            pa = sb + SM_P + (r7 & 3) * kPStride + (r7 >> 2) * 16 + mi * 32;
#pragma unroll 1
            for (int it = 0; it < 8; it++) {
                uint32_t pf[2][4];
                ldsm4(pf[0], pa);
                ldsm4(pf[1], pa + 128);
                pa += 256;
                const uint32_t base = acquire() + voff;
#pragma unroll
                for (int i = 0; i < 8; i++) {
#pragma unroll
                    for (int mt = 0; mt < 2; mt++) {
                        uint32_t vf[4];
                        ldsm4t(vf, (base ^ (mt * 32)) + (i >> 1) * 4096 + (i & 1) * 1024);
                        mma16816(O[2 * mt + (i & 1)], vf, pf[i >> 2][i & 2], pf[i >> 2][(i & 2) + 1]);
                    }
                }
                release();
            }
        }
        uint32_t ow[2];
#pragma unroll
        for (int mt = 0; mt < 2; mt++) {
            const float (&A)[4] = O[2 * mt];
            const float (&B)[4] = O[2 * mt + 1];
            const float lo = (t < 2 ? A[0] : B[1]) + __shfl_xor_sync(0xffffffffu, t < 2 ? A[1] : B[0], 2);
            const float hi = (t < 2 ? A[2] : B[3]) + __shfl_xor_sync(0xffffffffu, t < 2 ? A[3] : B[2], 2);
            ow[mt] = enc(pack_bf16(lo * fin, hi * fin));
        }
#pragma unroll
        for (int d = 0; d < 8; d++)
            asm volatile("st.relaxed.gpu.global.v2.u32 [%0], {%1,%2};" ::"l"(op + d * kHKV * 2048), "r"(ow[0]), "r"(ow[1]) : "memory");
        {
            uint32_t hf[7][4];
#pragma unroll
            for (int j = 0; j < 7; j++)
                ldsm4(hf[j], sb + SM_H + r7 * 512 + (2 * (j & 1) + (mi >> 1)) * 128 + (((2 * (j >> 1) + (mi & 1)) ^ r7) << 4));
            uint32_t wa2 = sb + SM_RING + (kW2N % kNSlot) * kSlot + (r7 + 8 * (mi >> 1)) * 128 + (((2 * w + (mi & 1)) ^ r7) << 4);
            uint32_t ya = mapa(sb + SM_Y + r * 256 + (16 * w + g) * 4, 2 * t), yb = mapa(bars + B_Y, 2 * t), wbar = bars + B_W2;
            const uint32_t ostep = mapa(bars + B_Y, 2 * t + 1) - yb;
            PIN(wa2); PIN(ya); PIN(yb); PIN(wbar);
            {
                mbar_wait(wbar, 0);
                float acc[4][4];
#pragma unroll
                for (int i = 0; i < 16; i++) acc[i >> 2][i & 3] = 0.f;
#pragma unroll
                for (int ks = 0; ks < 14; ks++) {
                    uint32_t af[4];
                    ldsm4t(af, wa2 + ks * 2048);
                    mma16816(acc[ks & 3], af, hf[ks >> 1][2 * (ks & 1)], hf[ks >> 1][2 * (ks & 1) + 1]);
                }
#pragma unroll
                for (int e = 0; e < 4; e++)
                    st_async(ya + (e & 1) * ostep + (e >> 1) * 32, __float_as_uint((acc[0][e] + acc[1][e]) + (acc[2][e] + acc[3][e])),
                             yb + (e & 1) * ostep);
            }
        }
    }
}

typedef CUresult (*EncodeFn)(CUtensorMap*, CUtensorMapDataType, cuuint32_t, void*, const cuuint64_t*, const cuuint64_t*,
                             const cuuint32_t*, const cuuint32_t*, CUtensorMapInterleave, CUtensorMapSwizzle,
                             CUtensorMapL2promotion, CUtensorMapFloatOOBfill);

void encode(EncodeFn fn, CUtensorMap* m, void* p, int rank, const cuuint64_t* dims, const cuuint64_t* strides,
            const cuuint32_t* box, CUtensorMapSwizzle sw = CU_TENSOR_MAP_SWIZZLE_128B) {
    const cuuint32_t es[4] = {1, 1, 1, 1};
    fn(m, CU_TENSOR_MAP_DATA_TYPE_BFLOAT16, rank, p, dims, strides, box, es, CU_TENSOR_MAP_INTERLEAVE_NONE,
       sw, CU_TENSOR_MAP_L2_PROMOTION_L2_256B, CU_TENSOR_MAP_FLOAT_OOB_FILL_NONE);
}

}

extern "C" void kernel_launch(void* const* d_in, const int* in_sizes, int n_in, void* d_out, int out_size) {
    (void)in_sizes; (void)n_in; (void)out_size;
    void* fnp = nullptr;
    cudaDriverEntryPointQueryResult qr;
    cudaGetDriverEntryPoint("cuTensorMapEncodeTiled", &fnp, cudaEnableDefault, &qr);
    EncodeFn fn = (EncodeFn)fnp;
    Params prm;
    {
        const cuuint64_t dims[3] = {64, (cuuint64_t)8 * kHKV * kSK, 2}, str[2] = {256, 128};
        const cuuint32_t box[3] = {64, 128, 2};
        encode(fn, &prm.m[0], d_in[1], 3, dims, str, box);
        encode(fn, &prm.m[1], d_in[2], 3, dims, str, box);
    }
    {
        const cuuint64_t dims[3] = {4096, 512, 1}, str[2] = {8192, 8192 * 512};
        const cuuint32_t box[3] = {64, 256, 1};
        encode(fn, &prm.m[2], d_in[3], 3, dims, str, box);
    }
    {
        const cuuint64_t dims[3] = {1792, 256, 2}, str[2] = {3584, 3584 * 256};
        const cuuint32_t box[3] = {32, 256, 2};
        encode(fn, &prm.m[3], d_in[6], 3, dims, str, box, CU_TENSOR_MAP_SWIZZLE_64B);
    }
    {
        const cuuint64_t dims[3] = {512, 1792, 1}, str[2] = {1024, 1024 * 1792};
        const cuuint32_t box[3] = {64, 224, 1};
        encode(fn, &prm.m[4], d_in[8], 3, dims, str, box);
    }
    {
        const cuuint64_t dims[4] = {512, 2, 8, 256}, str[3] = {8 * 1024, 1024, 16 * 1024};
        const cuuint32_t box[4] = {64, 2, 8, 8};
        encode(fn, &prm.m[5], d_in[4], 4, dims, str, box);
    }
    {
        int dev = 0, khz = 0, bits = 0;
        cudaGetDevice(&dev);
        cudaDeviceGetAttribute(&khz, cudaDevAttrMemoryClockRate, dev);
        cudaDeviceGetAttribute(&bits, cudaDevAttrGlobalMemoryBusWidth, dev);
        const double bytes_per_ns = 2.0 * khz * 1e-6 * bits / 8.0;
        const double scale = bytes_per_ns > 1000.0 ? (double)kGrid * kSlot / bytes_per_ns / kItemNs : 0.0;
        prm.sched_b = (int)(SCHED_B * scale + 0.5);
        prm.sched_a = (int)(SCHED_E * scale + 0.5) - (kItems - 1) * prm.sched_b;
    }
    cudaFuncSetAttribute(fused_decode_kernel, cudaFuncAttributeMaxDynamicSharedMemorySize, SM_BYTES);
    fused_decode_kernel<<<kGrid, kThreads, SM_BYTES>>>(
        (const __nv_bfloat16*)d_in[0], (const __nv_bfloat16*)d_in[7], (const __nv_bfloat16*)d_in[9],
        (__nv_bfloat16*)d_out, prm);
}
```

```cpp
#include <cuda_runtime.h>
#include <cuda_bf16.h>
#include <cuda.h>
#include <stdint.h>

namespace {

constexpr int kD = 512, kHKV = 8, kSK = 4096;
constexpr int kGrid = 64;
constexpr int kWarps = 14, kThreads = kWarps * 32;
constexpr int kSlot = 32768;
constexpr int kNSlot = 6;
constexpr int kItems = 70;
constexpr int kKVN = 3, kW2N = 67, kWoN = 68;
#define W_MAIN 4
#define LEAD 1
#define N_HEAD 6
#define HEAD_T0 900
#define HEAD_DT 550
#define SCHED_B 650
#define SCHED_E 43330
#define SCHED_D 325
#define SCHED_D2 240
#define OGATE_E 610
#define GO_N 40
constexpr int kWindow = W_MAIN, kWindowEnd = 3;
constexpr int kLead = LEAD;
constexpr int kGoN = GO_N;
constexpr int kHeadN = N_HEAD, kHeadT0 = HEAD_T0, kHeadDt = HEAD_DT;
constexpr int kGapW2 = SCHED_D, kGapWo = SCHED_D2, kGateO = OGATE_E - SCHED_D2;
constexpr double kItemNs = 625.6;
static_assert(kWindow >= 3 && kWindow < kNSlot && kNSlot <= 8 && kGoN < kKVN + 40, "ring");
static_assert(kWoN % kNSlot + 1 < kNSlot, "wo occupies two consecutive slots");

constexpr int kPStride = 2048 + 32;
constexpr int SM_RING = 0;
constexpr int SM_H = kNSlot * kSlot;
constexpr int SM_P = SM_H + 8 * 512;
constexpr int SM_X = SM_P + 4 * kPStride;
constexpr int SM_SCR = SM_X + 4 * kPStride;
constexpr int SM_Q = SM_SCR + 4 * 2176;
constexpr int SM_Y = SM_Q + 1024;
constexpr int SM_S = SM_Y + 2048;
constexpr int SM_ML = SM_S + 2048;
constexpr int SM_B1 = SM_ML + 64;
constexpr int SM_PROG = SM_B1 + 64;
constexpr int SM_BAR = SM_PROG + 32;
constexpr int B_FULL = 0, B_EMPTY = 8 * kNSlot, B_WO = 16 * kNSlot, B_W2 = B_WO + 32, B_GO = B_W2 + 8, B_GO2 = B_GO + 8,
              B_X = B_GO2 + 8, B_Q = B_X + 8, B_Y = B_Q + 8, B_S = B_Y + 8, B_H = B_S + 8, B_END = B_H + 8;
constexpr int SM_BYTES = SM_BAR + B_END;
static_assert(SM_BYTES <= 232448, "smem");

constexpr float kLog2e = 1.4426950408889634f;
constexpr uint32_t kSpinLimit = 1u << 22;
constexpr long long kWaitCycles = 1ll << 32;

struct Params {
    CUtensorMap m[6];
    int sched_a, sched_b;
};

__device__ __align__(128) uint32_t g_o[8][kHKV][2048];
__device__ __align__(128) uint32_t g_h[8][8][1024];

__device__ __forceinline__ uint32_t smem_u32(const void* p) { return (uint32_t)__cvta_generic_to_shared(p); }
__device__ __forceinline__ void mbar_init(uint32_t bar, uint32_t cnt) {
    asm volatile("mbarrier.init.shared::cta.b64 [%0], %1;" ::"r"(bar), "r"(cnt) : "memory");
}
__device__ __forceinline__ void mbar_expect_tx(uint32_t bar, uint32_t bytes) {
    asm volatile("mbarrier.arrive.expect_tx.shared::cta.b64 _, [%0], %1;" ::"r"(bar), "r"(bytes) : "memory");
}
__device__ __forceinline__ void mbar_arrive(uint32_t bar) {
    asm volatile("mbarrier.arrive.shared::cta.b64 _, [%0];" ::"r"(bar) : "memory");
}
__device__ __forceinline__ void mbar_arrive_n(uint32_t bar, uint32_t n) {
    asm volatile("mbarrier.arrive.shared::cta.b64 _, [%0], %1;" ::"r"(bar), "r"(n) : "memory");
}
__device__ __forceinline__ bool mbar_try(uint32_t bar, uint32_t parity) {
    uint32_t ok;
    asm volatile("{\n.reg .pred p;\nmbarrier.try_wait.parity.relaxed.cluster.shared::cta.b64 p, [%1], %2;\nselp.u32 %0, 1, 0, p;\n}"
                 : "=r"(ok) : "r"(bar), "r"(parity) : "memory");
    return ok != 0u;
}
__device__ __forceinline__ bool mbar_try_cta(uint32_t bar, uint32_t parity) {
    uint32_t ok;
    asm volatile("{\n.reg .pred p;\nmbarrier.try_wait.parity.shared::cta.b64 p, [%1], %2;\nselp.u32 %0, 1, 0, p;\n}"
                 : "=r"(ok) : "r"(bar), "r"(parity) : "memory");
    return ok != 0u;
}
__device__ __forceinline__ bool mbar_test(uint32_t bar, uint32_t parity) {
    uint32_t ok;
    asm volatile("{\n.reg .pred p;\nmbarrier.test_wait.parity.shared::cta.b64 p, [%1], %2;\nselp.u32 %0, 1, 0, p;\n}"
                 : "=r"(ok) : "r"(bar), "r"(parity) : "memory");
    return ok != 0u;
}
__device__ __forceinline__ void mbar_wait(uint32_t bar, uint32_t parity) {
    if (mbar_try_cta(bar, parity)) return;
    const long long t0 = clock64();
    while (!mbar_try_cta(bar, parity))
        if (clock64() - t0 > kWaitCycles) __trap();
}
__device__ __forceinline__ void mbar_wait_cl(uint32_t bar, uint32_t parity) {
    if (!mbar_try(bar, parity)) {
        const long long t0 = clock64();
        while (!mbar_try(bar, parity))
            if (clock64() - t0 > kWaitCycles) __trap();
    }
    asm volatile("fence.acquire.sync_restrict::shared::cluster.cluster;" ::: "memory");
}
#define PIN(x) asm volatile("shfl.sync.bfly.b32 %0, %0, 0, 0x1f, 0xffffffff;" : "+r"(x) :: "memory")
#define PINF(x) asm volatile("" : "+f"(x) :: "memory")
#define PINL(x) asm volatile("{\n.reg .b32 lo, hi;\nmov.b64 {lo, hi}, %0;\nshfl.sync.bfly.b32 lo, lo, 0, 0x1f, 0xffffffff;\n" \
                             "shfl.sync.bfly.b32 hi, hi, 0, 0x1f, 0xffffffff;\nmov.b64 %0, {lo, hi};\n}" : "+l"(x) :: "memory")
__device__ __forceinline__ void tma4d(uint32_t dst, const CUtensorMap* m, int c0, int c1, int c2, int c3, uint32_t bar) {
    asm volatile("cp.async.bulk.tensor.4d.shared::cluster.global.mbarrier::complete_tx::bytes [%0], [%1, {%3, %4, %5, %6}], [%2];"
                 ::"r"(dst), "l"(m), "r"(bar), "r"(c0), "r"(c1), "r"(c2), "r"(c3) : "memory");
}
__device__ __forceinline__ void tma3d(uint32_t dst, const CUtensorMap* m, int c0, int c1, int c2, uint32_t bar) {
    asm volatile("cp.async.bulk.tensor.3d.shared::cluster.global.mbarrier::complete_tx::bytes [%0], [%1, {%3, %4, %5}], [%2];"
                 ::"r"(dst), "l"(m), "r"(bar), "r"(c0), "r"(c1), "r"(c2) : "memory");
}
__device__ __forceinline__ void tma3d_hint(uint32_t dst, const CUtensorMap* m, int c0, int c1, int c2, uint32_t bar, uint64_t pol) {
    asm volatile("cp.async.bulk.tensor.3d.shared::cluster.global.mbarrier::complete_tx::bytes.L2::cache_hint [%0], [%1, {%3, %4, %5}], [%2], %6;"
                 ::"r"(dst), "l"(m), "r"(bar), "r"(c0), "r"(c1), "r"(c2), "l"(pol) : "memory");
}
__device__ __forceinline__ void bar_sync(int id, int n) { asm volatile("barrier.sync %0, %1;" ::"r"(id), "r"(n) : "memory"); }
__device__ __forceinline__ bool elect_one() {
    uint32_t p;
    asm volatile("{\n.reg .pred p;\nelect.sync _|p, 0xffffffff;\nselp.u32 %0, 1, 0, p;\n}" : "=r"(p));
    return p != 0u;
}
__device__ __forceinline__ void cluster_arrive() { asm volatile("barrier.cluster.arrive.relaxed;" ::: "memory"); }
__device__ __forceinline__ void cluster_wait() { asm volatile("barrier.cluster.wait;" ::: "memory"); }
__device__ __forceinline__ uint32_t mapa(uint32_t a, uint32_t rank) {
    uint32_t d;
    asm("mapa.shared::cluster.u32 %0, %1, %2;" : "=r"(d) : "r"(a), "r"(rank));
    return d;
}
__device__ __forceinline__ void st_async(uint32_t a, uint32_t v, uint32_t bar) {
    asm volatile("st.async.shared::cluster.mbarrier::complete_tx::bytes.u32 [%0], %1, [%2];" ::"r"(a), "r"(v), "r"(bar) : "memory");
}
__device__ __forceinline__ void st_async2_pred(uint32_t a, float x, float y, uint32_t bar, bool c) {
    asm volatile("{\n.reg .pred p;\nsetp.ne.u32 p, %4, 0;\n@p st.async.shared::cluster.mbarrier::complete_tx::bytes.v2.f32 [%0], {%1,%2}, [%3];\n}"
                 ::"r"(a), "f"(x), "f"(y), "r"(bar), "r"((uint32_t)c) : "memory");
}
__device__ __forceinline__ void st_async4(uint32_t a, uint32_t x, uint32_t y, uint32_t z, uint32_t w, uint32_t bar) {
    asm volatile("st.async.shared::cluster.mbarrier::complete_tx::bytes.v4.u32 [%0], {%1,%2,%3,%4}, [%5];"
                 ::"r"(a), "r"(x), "r"(y), "r"(z), "r"(w), "r"(bar) : "memory");
}

__device__ __forceinline__ void ldsm4(uint32_t (&r)[4], uint32_t a) {
    asm volatile("ldmatrix.sync.aligned.m8n8.x4.shared.b16 {%0,%1,%2,%3}, [%4];"
                 : "=r"(r[0]), "=r"(r[1]), "=r"(r[2]), "=r"(r[3]) : "r"(a) : "memory");
}
__device__ __forceinline__ void ldsm4t(uint32_t (&r)[4], uint32_t a) {
    asm volatile("ldmatrix.sync.aligned.m8n8.x4.trans.shared.b16 {%0,%1,%2,%3}, [%4];"
                 : "=r"(r[0]), "=r"(r[1]), "=r"(r[2]), "=r"(r[3]) : "r"(a) : "memory");
}
__device__ __forceinline__ void mma16816(float (&c)[4], const uint32_t (&a)[4], uint32_t b0, uint32_t b1) {
    asm volatile("mma.sync.aligned.m16n8k16.row.col.f32.bf16.bf16.f32 {%0,%1,%2,%3}, {%4,%5,%6,%7}, {%8,%9}, {%0,%1,%2,%3};"
                 : "+f"(c[0]), "+f"(c[1]), "+f"(c[2]), "+f"(c[3])
                 : "r"(a[0]), "r"(a[1]), "r"(a[2]), "r"(a[3]), "r"(b0), "r"(b1));
}
__device__ __forceinline__ uint32_t movm(uint32_t a) {
    uint32_t d;
    asm volatile("movmatrix.sync.aligned.m8n8.trans.b16 %0, %1;" : "=r"(d) : "r"(a));
    return d;
}
__device__ __forceinline__ uint32_t pack_bf16(float lo, float hi) {
    uint32_t d;
    asm("cvt.rn.bf16x2.f32 %0, %1, %2;" : "=r"(d) : "f"(hi), "f"(lo));
    return d;
}
__device__ __forceinline__ float bf_lo(uint32_t u) { return __uint_as_float(u << 16); }
__device__ __forceinline__ float bf_hi(uint32_t u) { return __uint_as_float(u & 0xffff0000u); }
__device__ __forceinline__ float bfr(float v) { return __uint_as_float(pack_bf16(0.f, v)); }
__device__ __forceinline__ uint32_t max_bf16x2(uint32_t a, uint32_t b) {
    uint32_t d;
    asm("max.bf16x2 %0, %1, %2;" : "=r"(d) : "r"(a), "r"(b));
    return d;
}
__device__ __forceinline__ float ex2(float x) {
    float y;
    asm("ex2.approx.ftz.f32 %0, %1;" : "=f"(y) : "f"(x));
    return y;
}
__device__ __forceinline__ float mul_sigmoid(float v, float z) { return __fdividef(v, 1.0f + ex2(fminf(-kLog2e * z, 120.f))); }
__device__ __forceinline__ uint32_t lds32(uint32_t a) { uint32_t v; asm volatile("ld.shared.u32 %0, [%1];" : "=r"(v) : "r"(a) : "memory"); return v; }
__device__ __forceinline__ float2 ldsf2(uint32_t a) { float2 v; asm volatile("ld.shared.v2.f32 {%0,%1}, [%2];" : "=f"(v.x), "=f"(v.y) : "r"(a) : "memory"); return v; }
__device__ __forceinline__ uint4 lds128(uint32_t a) {
    uint4 v;
    asm volatile("ld.shared.v4.u32 {%0,%1,%2,%3}, [%4];" : "=r"(v.x), "=r"(v.y), "=r"(v.z), "=r"(v.w) : "r"(a) : "memory");
    return v;
}
__device__ __forceinline__ void sts32(uint32_t a, uint32_t v) { asm volatile("st.shared.u32 [%0], %1;" ::"r"(a), "r"(v) : "memory"); }
__device__ __forceinline__ void stsf(uint32_t a, float v) { asm volatile("st.shared.f32 [%0], %1;" ::"r"(a), "f"(v) : "memory"); }
__device__ __forceinline__ void sts128(uint32_t a, uint32_t x, uint32_t y, uint32_t z, uint32_t w) {
    asm volatile("st.shared.v4.u32 [%0], {%1,%2,%3,%4};" ::"r"(a), "r"(x), "r"(y), "r"(z), "r"(w) : "memory");
}
__device__ __forceinline__ uint32_t enc(uint32_t b) { return b == 0u ? 0x80000000u : b; }
__device__ __forceinline__ void st_pred32(void* p, uint32_t v, bool c) {
    asm volatile("{\n.reg .pred p;\nsetp.ne.u32 p, %2, 0;\n@p st.global.u32 [%0], %1;\n}" ::"l"(p), "r"(v), "r"((uint32_t)c) : "memory");
}
__device__ __forceinline__ void ld_rlx4_pred(uint32_t (&v)[4], const uint32_t* p, bool c) {
    asm volatile("{\n.reg .pred p;\nsetp.ne.u32 p, %5, 0;\n@p ld.relaxed.gpu.global.v4.u32 {%0,%1,%2,%3}, [%4];\n}"
                 : "+r"(v[0]), "+r"(v[1]), "+r"(v[2]), "+r"(v[3]) : "l"(p), "r"((uint32_t)c) : "memory");
}
__device__ __forceinline__ uint32_t gt32() { uint32_t c; asm volatile("mov.u32 %0, %globaltimer_lo;" : "=r"(c) :: "memory"); return c; }
__device__ __forceinline__ void wait_until(uint32_t t0, int ns) {
    while (gt32() - t0 < (uint32_t)max(ns, 0)) {}
}
__device__ __forceinline__ uint32_t ldg32(const void* p) {
    uint32_t v;
    asm volatile("ld.global.nc.u32 %0, [%1];" : "=r"(v) : "l"(p));
    return v;
}

__global__ void __cluster_dims__(8, 1, 1) __launch_bounds__(kThreads, 1)
fused_decode_kernel(const __nv_bfloat16* __restrict__ x, const __nv_bfloat16* __restrict__ b1,
                    const __nv_bfloat16* __restrict__ b2, __nv_bfloat16* __restrict__ out,
                    const __grid_constant__ Params prm) {
    extern __shared__ __align__(1024) unsigned char smem_raw[];
    const uint32_t sb = smem_u32(smem_raw);
    const uint32_t bars = sb + SM_BAR;
    const int tid = threadIdx.x, wid = tid >> 5, lane = tid & 31;
    const int hkv = blockIdx.x >> 3, r = blockIdx.x & 7;
    if (tid < 32) {
        if (elect_one()) {
            mbar_init(bars + B_FULL, 1);
            mbar_init(bars + B_FULL + 8, 1);
            asm volatile("fence.mbarrier_init.release.cluster;" ::: "memory");
#pragma unroll
            for (int n = 0; n < 2; n++) {
                mbar_expect_tx(bars + B_FULL + 8 * n, kSlot);
                tma3d(sb + SM_RING + n * kSlot, &prm.m[2], blockIdx.x * 64, n * 256, 0, bars + B_FULL + 8 * n);
            }
#pragma unroll
            for (int n = 2; n < kNSlot; n++) mbar_init(bars + B_FULL + 8 * n, 1);
            asm volatile("fence.mbarrier_init.release.cluster;" ::: "memory");
            mbar_expect_tx(bars + B_FULL + 16, r < 7 ? kSlot : 0);
            if (r < 7) tma3d(sb + SM_RING + 2 * kSlot, &prm.m[3], hkv * 224 + r * 32, 0, 0, bars + B_FULL + 16);
        }
    }
    const uint32_t t_start = gt32();
    if (wid == 1) asm volatile("prefetch.global.L1 [%0];" ::"l"(x + r * kD + lane * 16) : "memory");
    if (wid == 3 && lane < 4) asm volatile("prefetch.tensormap [%0];" ::"l"(&prm.m[lane + (lane & 2)]) : "memory");
    if (tid == 64) {
        if (sb & 1023u) __trap();
#pragma unroll
        for (int n = 0; n < kNSlot; n++) mbar_init(bars + B_EMPTY + 8 * n, 8);
#pragma unroll
        for (int n = B_WO; n < B_END; n += 8) mbar_init(bars + n, n < B_H ? 1 : 8);
        asm volatile("fence.mbarrier_init.release.cluster;" ::: "memory");
        sts128(sb + SM_PROG, 0, 0, 0, 0);
        sts128(sb + SM_PROG + 16, 0, 0, 0, 0);
        asm volatile("fence.release.sync_restrict::shared::cta.cluster;" ::: "memory");
        mbar_expect_tx(bars + B_X, 8192);
        mbar_expect_tx(bars + B_Q, 1024);
        mbar_expect_tx(bars + B_Y, 2048);
        mbar_expect_tx(bars + B_S, 2048);
    }
    __syncwarp();
    cluster_arrive();
    const int w = (wid - 2) & 7;
    const int g = lane >> 2, t = lane & 3, r7 = lane & 7, mi = lane >> 3;

    if (wid == 1) {
        {
            const uint4* xr = reinterpret_cast<const uint4*>(x + r * kD) + lane;
            const uint4 xv0 = __ldg(xr), xv1 = __ldg(xr + 32);
            float f[16];
            const uint32_t u[8] = {xv0.x, xv0.y, xv0.z, xv0.w, xv1.x, xv1.y, xv1.z, xv1.w};
#pragma unroll
            for (int i = 0; i < 8; i++) { f[2 * i] = bf_lo(u[i]); f[2 * i + 1] = bf_hi(u[i]); }
            float s = 0.f;
#pragma unroll
            for (int i = 0; i < 16; i++) s += f[i];
#pragma unroll
            for (int o = 16; o; o >>= 1) s += __shfl_xor_sync(0xffffffffu, s, o);
            const float mean = s * (1.0f / kD);
            float vs = 0.f;
#pragma unroll
            for (int i = 0; i < 16; i++) { const float d = f[i] - mean; vs = fmaf(d, d, vs); }
#pragma unroll
            for (int o = 16; o; o >>= 1) vs += __shfl_xor_sync(0xffffffffu, vs, o);
            const float mb = bfr(mean);
            const float den = bfr(__fsqrt_rn(bfr(bfr(vs * (1.0f / kD)) + 1e-5f)));
            const float rden = __frcp_rn(den);
            uint32_t q[8];
#pragma unroll
            for (int i = 0; i < 8; i++) {
                const uint32_t d2 = pack_bf16(f[2 * i] - mb, f[2 * i + 1] - mb);
                q[i] = pack_bf16(bf_lo(d2) * rden, bf_hi(d2) * rden);
            }
            const uint32_t xoff = SM_X + r * 1024 + ((lane >> 1) & 7) * 128 + (((2 * (lane >> 4) + (lane & 1)) ^ r) << 4);
            cluster_wait();
#pragma unroll 1
            for (int d = 0; d < 8; d++) {
                const uint32_t rb = mapa(sb, d), xa = rb + xoff;
                st_async4(xa, q[0], q[1], q[2], q[3], rb + SM_BAR + B_X);
                st_async4(xa ^ 64, q[4], q[5], q[6], q[7], rb + SM_BAR + B_X);
            }
        }
        const int col = hkv * 64 + 2 * lane;
        const uint32_t xw = ldg32(x + r * kD + col), bw = ldg32(b2 + col);
        __nv_bfloat16* dst = out + r * kD + col;
        uint32_t pa = sb + SM_Y + lane * 8, pbar = bars + B_Y;
        PINL(dst);
        float g0 = 0.f, g1 = 0.f;
#pragma unroll 1
        for (int pass = 0; pass < 2; pass++) {
            mbar_wait_cl(pbar, 0);
            float2 v[8];
#pragma unroll
            for (int c = 0; c < 8; c++) v[c] = ldsf2(pa + c * 256);
            const uint32_t sw = pack_bf16(((v[0].x + v[1].x) + (v[2].x + v[3].x)) + ((v[4].x + v[5].x) + (v[6].x + v[7].x)),
                                          ((v[0].y + v[1].y) + (v[2].y + v[3].y)) + ((v[4].y + v[5].y) + (v[6].y + v[7].y)));
            const uint32_t pw = pack_bf16(bf_lo(sw) * g0, bf_hi(sw) * g1);
            st_pred32(dst, pack_bf16(bf_lo(xw) + bf_lo(pw), bf_hi(xw) + bf_hi(pw)), pass);
            if (pass) break;
            const uint32_t yw = pack_bf16(bf_lo(sw) + bf_lo(bw), bf_hi(sw) + bf_hi(bw));
            const uint32_t gw = pack_bf16(mul_sigmoid(bf_lo(yw), bf_lo(yw)), mul_sigmoid(bf_hi(yw), bf_hi(yw)));
            g0 = bf_lo(gw);
            g1 = bf_hi(gw);
            pa = sb + SM_S + lane * 8;
            pbar = bars + B_S;
        }
    } else if (wid == 0) {
        cluster_wait();
        const int kvrow0 = (r * kHKV + hkv) * kSK;
        const uint32_t prog_remote = mapa(sb + SM_PROG + r * 4, lane & 7);
        uint64_t stream_pol;
        asm volatile("createpolicy.fractional.L2::evict_first.b64 %0, 1.0;" : "=l"(stream_pol));
        int slot = kKVN, ph = 0;
        int landed = 0, lslot = 0, lph = 0;
#pragma unroll 1
        for (int n = kKVN; n < kItems; n++) {
            if (n >= kNSlot) mbar_wait(bars + B_EMPTY + 8 * slot, ph ^ 1);
            for (const int need = n - (n >= kW2N ? kWindowEnd : kWindow); landed <= need; landed++) {
                mbar_wait(bars + B_FULL + 8 * lslot, lph);
                if (++lslot == kNSlot) { lslot = 0; lph ^= 1; }
            }
            wait_until(t_start, n < kHeadN ? kHeadT0 + (n - kKVN) * kHeadDt
                                           : prm.sched_a + n * prm.sched_b + (n < kW2N ? 0 : n < kWoN ? kGapW2 : kGapWo));
            if (n < kW2N) {
                if (lane < 8) asm volatile("st.relaxed.cluster.shared::cluster.u32 [%0], %1;" ::"r"(prog_remote), "r"(n) : "memory");
                for (uint32_t it = 0;; it++) {
                    int p;
                    asm volatile("ld.relaxed.cluster.shared::cta.u32 %0, [%1];" : "=r"(p) : "r"(sb + SM_PROG + (lane & 7) * 4) : "memory");
                    if (__all_sync(0xffffffffu, max(p, kKVN) + kLead >= n)) break;
                    if (it > kSpinLimit * 16) __trap();
                }
            }
            if (elect_one()) {
                const uint32_t dst = sb + SM_RING + slot * kSlot;
                if (n < kW2N) {
                    const int u = n - kKVN;
                    mbar_expect_tx(bars + B_FULL + 8 * slot, kSlot);
                    tma3d_hint(dst, &prm.m[(u >> 4) & 1], 0, 0, kvrow0 + (u >> 5) * 2048 + (u & 15) * 128, bars + B_FULL + 8 * slot, stream_pol);
                } else if (n >= kWoN) {
                    const uint32_t wb = bars + B_WO + 16 * (n - kWoN);
                    mbar_expect_tx(wb, kSlot / 2);
                    tma4d(dst, &prm.m[5], hkv * 64, 0, 0, r * 32 + (n - kWoN) * 16, wb);
                    mbar_expect_tx(wb + 8, kSlot / 2);
                    tma4d(dst + kSlot / 2, &prm.m[5], hkv * 64, 0, 0, r * 32 + (n - kWoN) * 16 + 8, wb + 8);
                } else {
                    mbar_expect_tx(bars + B_W2, 224 * 128);
                    tma3d(dst, &prm.m[4], hkv * 64, r * 224, 0, bars + B_W2);
                }
                if (n == kGoN) mbar_arrive(bars + B_GO);
            }
            __syncwarp();
            if (++slot == kNSlot) { slot = 0; ph ^= 1; }
        }
        wait_until(gt32(), kGateO);
        mbar_wait(bars + B_W2, 0);
        if (lane == 0) mbar_arrive(bars + B_GO2);
    } else if (wid < 10) {
        const int kg = w >> 1, ch = w & 1;
        if (w == 7 && lane < 16) sts32(sb + SM_B1 + lane * 4, ldg32(b1 + hkv * 224 + (r < 7 ? r : 0) * 32 + 2 * lane));
        uint32_t wa = sb + SM_SCR + kg * 2176 + t * 544 + (ch * 32 + g) * 4;
        uint32_t ra = sb + SM_SCR + w * 272 + lane * 8;
        uint32_t* op = &g_o[hkv][r][kg * 512 + lane * 4];
        const uint32_t baddr = sb + SM_X + r7 * 1024 + (mi & 1) * 512 + (((2 * kg + (mi >> 1)) ^ r7) << 4);
        uint32_t abase = sb + SM_RING + kg * (kSlot / 2) + (r7 + 64 * (mi >> 1)) * 128 + (((4 * ch + (mi & 1)) ^ r7) << 4);
        uint32_t abar = bars + B_FULL + 8 * (kg >> 1);
        uint32_t sa = mapa(sb + SM_S + r * 256 + lane * 8, w), sbar = mapa(bars + B_S, w);
        PIN(wa); PIN(ra); PINL(op); PIN(sa); PIN(sbar);
        uint32_t bf[4][4];
        auto fetch_o = [&]() {
            bool all = true;
#pragma unroll
            for (int j = 0; j < 4; j++) {
                const bool ok = bf[j][0] != 0u && bf[j][1] != 0u && bf[j][2] != 0u && bf[j][3] != 0u;
                all = all && ok;
                ld_rlx4_pred(bf[j], op + j * 128, !ok);
            }
            return __all_sync(0xffffffffu, all);
        };
        cluster_wait();
        mbar_wait_cl(bars + B_X, 0);
#pragma unroll 1
        for (int pass = 0; pass < 3; pass++) {
            float acc[2][2][4];
#pragma unroll
            for (int i = 0; i < 16; i++) acc[i >> 3][(i >> 2) & 1][i & 3] = 0.f;
            bool stream = true;
            if (pass == 2) {
                mbar_wait(bars + B_GO2, 0);
                for (uint32_t it = 0;; it++) {
                    stream = fetch_o();
                    if (stream || kg < 2 || __all_sync(0xffffffffu, mbar_test(abar, 0))) break;
                    if (it > kSpinLimit) __trap();
                }
            } else {
#pragma unroll
                for (int i = 0; i < 4; i++) ldsm4(bf[i], baddr + ((i + 2 * (pass & ch)) & 3) * 128);
            }
            if (pass == 1) {
                const uint32_t a1 = sb + SM_RING + 2 * kSlot + (128 * kg + 32 * ch + r7 + 64 * (mi >> 1)) * 64 + (((mi & 1) ^ (r7 >> 1)) << 4);
                mbar_wait(bars + B_FULL + 16, 0);
#pragma unroll
                for (int ks = 0; ks < 4; ks++) {
#pragma unroll
                    for (int mt = 0; mt < 2; mt++) {
                        uint32_t af[4];
                        ldsm4t(af, (a1 ^ (mt * 32)) + (ks >> 1) * 1024 + (ks & 1) * 512);
                        mma16816(acc[mt][ks & 1], af, bf[ks >> 1][2 * (ks & 1)], bf[ks >> 1][2 * (ks & 1) + 1]);
                    }
                }
            } else if (stream) {
                mbar_wait(abar, 0);
#pragma unroll
                for (int ks = 0; ks < 8; ks++) {
#pragma unroll
                    for (int mt = 0; mt < 2; mt++) {
                        uint32_t af[4];
                        ldsm4t(af, (abase ^ (mt * 32)) + ks * 1024);
                        mma16816(acc[mt][ks & 1], af, bf[ks >> 1][2 * (ks & 1)], bf[ks >> 1][2 * (ks & 1) + 1]);
                    }
                }
            } else {
                uint32_t af[8][2][4];
                mbar_wait(abar, 0);
#pragma unroll
                for (int ks = 0; ks < 8; ks++) {
                    ldsm4t(af[ks][0], abase + ks * 1024);
                    ldsm4t(af[ks][1], (abase ^ 32) + ks * 1024);
                }
                for (uint32_t it = 0; !fetch_o(); it++)
                    if (it > kSpinLimit) __trap();
#pragma unroll
                for (int ks = 0; ks < 8; ks++) {
                    mma16816(acc[0][ks & 1], af[ks][0], bf[ks >> 1][2 * (ks & 1)], bf[ks >> 1][2 * (ks & 1) + 1]);
                    mma16816(acc[1][ks & 1], af[ks][1], bf[ks >> 1][2 * (ks & 1)], bf[ks >> 1][2 * (ks & 1) + 1]);
                }
            }
#pragma unroll
            for (int mt = 0; mt < 2; mt++) {
#pragma unroll
                for (int e = 0; e < 4; e++)
                    stsf(wa + (e & 1) * 272 + (mt * 16 + 8 * (e >> 1)) * 4, acc[mt][0][e] + acc[mt][1][e]);
            }
            bar_sync(1, 256);
            const float2 p0 = ldsf2(ra), p1 = ldsf2(ra + 2176), p2 = ldsf2(ra + 2 * 2176), p3 = ldsf2(ra + 3 * 2176);
            float s0 = (p0.x + p1.x) + (p2.x + p3.x), s1 = (p0.y + p1.y) + (p2.y + p3.y);
            st_async2_pred(sa, s0, s1, sbar, pass == 2);
            if (pass == 2) break;
            if (pass == 0) {
                const uint32_t rb = mapa(sb, w);
                st_async(rb + SM_Q + (r * 32 + lane) * 4, pack_bf16(s0, s1), rb + SM_BAR + B_Q);
                if (lane == 0) mbar_arrive_n(bars + B_EMPTY + 8 * (kg >> 1), 2);
            } else {
                if (lane == 0) mbar_arrive(bars + B_EMPTY + 16);
                s0 += __shfl_xor_sync(0xffffffffu, s0, 16);
                s1 += __shfl_xor_sync(0xffffffffu, s1, 16);
                const uint32_t sw = pack_bf16(s0, s1), b1w = lds32(sb + SM_B1 + (lane & 15) * 4);
                const uint32_t vw = pack_bf16(bf_lo(sw) + bf_lo(b1w), bf_hi(sw) + bf_hi(b1w));
                const float v0 = bf_lo(vw), v1 = bf_hi(vw);
                const float c = 2.0f * 0.7978845608028654f;
                uint32_t hw = pack_bf16(mul_sigmoid(v0, c * (v0 + 0.044715f * v0 * v0 * v0)),
                                        mul_sigmoid(v1, c * (v1 + 0.044715f * v1 * v1 * v1)));
                hw = r < 7 ? enc(hw) : 0x80000000u;
                {
                    uint32_t* cp = &g_o[w][hkv][(g * 16 + r) * 16 + t * 4];
                    *reinterpret_cast<uint4*>(cp) = make_uint4(0u, 0u, 0u, 0u);
                    *reinterpret_cast<uint4*>(cp + 128) = make_uint4(0u, 0u, 0u, 0u);
                    __threadfence();
                    bar_sync(1, 256);
                }
                {
                    uint32_t* hp = &g_h[(lane >> 4) * 4][hkv][w * 128 + (2 * (r & 1) + (mi & 1)) * 32 + (((2 * (r >> 1) + (r7 >> 2)) ^ w) << 2) + t];
#pragma unroll
                    for (int d = 0; d < 4; d++) asm volatile("st.relaxed.gpu.global.u32 [%0], %1;" ::"l"(hp + d * 8 * 1024), "r"(hw) : "memory");
                }
                mbar_wait(bars + B_GO, 0);
                {
                    uint32_t* hp = &g_h[hkv][r][w * 128 + lane * 4];
                    uint4 v;
                    for (uint32_t it = 0;; it++) {
                        asm volatile("ld.relaxed.gpu.global.v4.u32 {%0,%1,%2,%3}, [%4];" : "=r"(v.x), "=r"(v.y), "=r"(v.z), "=r"(v.w) : "l"(hp) : "memory");
                        if (v.x != 0u && v.y != 0u && v.z != 0u && v.w != 0u) break;
                        if (it > kSpinLimit) __trap();
                    }
                    sts128(sb + SM_H + w * 512 + lane * 16, v.x, v.y, v.z, v.w);
                    *reinterpret_cast<uint4*>(hp) = make_uint4(0u, 0u, 0u, 0u);
                    __threadfence();
                }
                __syncwarp();
                if (lane == 0) mbar_arrive(bars + B_H);
#pragma unroll
                for (int i = 0; i < 16; i++) bf[i >> 2][i & 3] = 0u;
                abase += (kWoN % kNSlot) * kSlot;
                abar = bars + B_WO + 8 * kg;
                PIN(abase); PIN(abar);
            }
            bar_sync(1, 256);
        }
    } else {
        int slot = kKVN, ph = 0;
        auto acquire = [&]() {
            mbar_wait(bars + B_FULL + 8 * slot, ph);
            return sb + SM_RING + slot * kSlot;
        };
        auto release = [&]() {
            __syncwarp();
            if (lane == 0) mbar_arrive_n(bars + B_EMPTY + 8 * slot, 2);
            if (++slot == kNSlot) { slot = 0; ph ^= 1; }
        };
        const int hl = r7 >> 2;
        const bool diag = (g >> 2) == (t >> 1);
        uint32_t koff[4];
#pragma unroll
        for (int c = 0; c < 4; c++)
            koff[c] = (w * 32 + r7 + 8 * (mi & 1)) * 256 + hl * 128 + (((2 * c + (mi >> 1)) ^ (2 * (r7 & 3) + hl)) << 4);
        const uint32_t voff = (16 * (mi >> 1) + r7 + 8 * hl) * 256 + hl * 128 + (((2 * w + (mi & 1)) ^ (2 * (r7 & 3) + hl)) << 4);
        const int ht = 2 * (t & 1) + (t >> 1);
        uint32_t* op = &g_o[0][hkv][((ht * 4 + w) * 8 + r) * 16 + (g & 3) * 4 + 2 * (g >> 2)];
        PINL(op);
        cluster_wait();
        uint32_t qf[8][2];
        mbar_wait_cl(bars + B_Q, 0);
#pragma unroll
        for (int ks = 0; ks < 8; ks++) {
            qf[ks][0] = lds32(sb + SM_Q + ((g & 3) * 64 + (ks ^ (g & 4)) * 8 + t) * 4);
            qf[ks][1] = lds32(sb + SM_Q + ((g & 3) * 64 + (ks ^ (g & 4)) * 8 + 4 + t) * 4);
        }
        uint32_t mx2 = 0xff7fff7fu;
        uint32_t mprev = 0xff7fff7fu;
        float Mw = bf_hi(mprev), l = 0.f, fin = 0.f;
        float O[4][4];
#pragma unroll
        for (int i = 0; i < 4; i++) { O[i][0] = O[i][1] = O[i][2] = O[i][3] = 0.f; }
#pragma unroll 1
        for (int c = 0; c < 2; c++) {
            uint32_t pa = sb + SM_P + (g & 3) * kPStride + (diag ? 0 : 16) + t * 4 + w * 64;
#pragma unroll 1
            for (int it = 0; it < 16; it++) {
                const uint32_t base = acquire();
                float sc[2][2][4];
#pragma unroll
                for (int i = 0; i < 16; i++) sc[i >> 3][(i >> 2) & 1][i & 3] = 0.f;
#pragma unroll
                for (int ks = 0; ks < 8; ks++) {
#pragma unroll
                    for (int mt = 0; mt < 2; mt++) {
                        uint32_t kf[4];
                        ldsm4(kf, base + (koff[ks & 3] ^ ((ks >> 2) * 144)) + mt * 4096);
                        mma16816(sc[mt][ks & 1], kf, qf[ks][0], qf[ks][1]);
                    }
                }
                release();
#pragma unroll
                for (int mt = 0; mt < 2; mt++) {
                    const uint32_t sa = pack_bf16(sc[mt][0][0] + sc[mt][1][0], sc[mt][0][1] + sc[mt][1][1]);
                    const uint32_t sx = __shfl_xor_sync(0xffffffffu, pack_bf16(sc[mt][0][2] + sc[mt][1][2], sc[mt][0][3] + sc[mt][1][3]), 2);
                    const uint32_t s2 = diag ? sa : sx;
                    const float scale = 0.08838834764831845f;
                    const uint32_t v = pack_bf16(bf_lo(s2) * scale, bf_hi(s2) * scale);
                    mx2 = max_bf16x2(mx2, v);
                    sts32(pa + mt * 32, movm(v));
                }
                pa += it == 7 ? 4 * kPStride - 7 * 256 : 256;
            }
            {
#pragma unroll
                for (int o = 2; o <= 16; o <<= 1) mx2 = max_bf16x2(mx2, __shfl_xor_sync(0xffffffffu, mx2, o));
                if (lane < 2) sts32(sb + SM_ML + lane * 16 + w * 4, mx2);
                bar_sync(2, 128);
                const uint4 a0 = lds128(sb + SM_ML), b0 = lds128(sb + SM_ML + 16);
                const uint32_t m01 = max_bf16x2(max_bf16x2(a0.x, a0.y), max_bf16x2(a0.z, a0.w));
                const uint32_t m23 = max_bf16x2(max_bf16x2(b0.x, b0.y), max_bf16x2(b0.z, b0.w));
                const uint32_t mw = (w & 2) ? m23 : m01, mt = (t & 1) ? m23 : m01;
                const float M = (w & 1) ? bf_hi(mw) : bf_lo(mw);
                l *= ex2((Mw - M) * kLog2e);
                Mw = M;
                const float al0 = ex2((bf_lo(mprev) - bf_lo(mt)) * kLog2e), al1 = ex2((bf_hi(mprev) - bf_hi(mt)) * kLog2e);
                mprev = mt;
#pragma unroll
                for (int i = 0; i < 4; i++) { O[i][0] *= al0; O[i][1] *= al1; O[i][2] *= al0; O[i][3] *= al1; }
                const uint32_t ea = sb + SM_P + w * kPStride + lane * 16;
#pragma unroll 2
                for (int i = 0; i < 8; i++) {
                    const uint32_t ei = ea + (i >> 2) * (4 * kPStride) + (i & 3) * 512;
                    const uint4 sv = lds128(ei);
                    const uint32_t uu[4] = {sv.x, sv.y, sv.z, sv.w};
                    uint32_t rr[4];
#pragma unroll
                    for (int e = 0; e < 4; e++) {
                        const float p0 = ex2((bf_lo(uu[e]) - M) * kLog2e), p1 = ex2((bf_hi(uu[e]) - M) * kLog2e);
                        l += p0 + p1;
                        rr[e] = pack_bf16(p0, p1);
                    }
                    sts128(ei, rr[0], rr[1], rr[2], rr[3]);
                }
                float ls = l;
#pragma unroll
                for (int o = 16; o; o >>= 1) ls += __shfl_xor_sync(0xffffffffu, ls, o);
                if (lane == 0) stsf(sb + SM_ML + 32 + w * 4, ls);
                bar_sync(2, 128);
                fin = __fdividef(1.0f, __uint_as_float(lds32(sb + SM_ML + 32 + ht * 4)));
                PINF(fin);
                if (c == 1) mbar_wait(bars + B_H, 0);
            }
            pa = sb + SM_P + (r7 & 3) * kPStride + (r7 >> 2) * 16 + mi * 32;
#pragma unroll 1
            for (int it = 0; it < 16; it++) {
                uint32_t pf[2][4], ps[2][8];
                ldsm4(pf[0], pa);
                ldsm4(pf[1], pa + 128);
                pa += it == 7 ? 4 * kPStride - 7 * 256 : 256;
#pragma unroll
                for (int i = 0; i < 8; i++) {
                    ps[0][i] = diag ? pf[i >> 2][i & 3] : 0u;
                    ps[1][i] = diag ? 0u : pf[i >> 2][i & 3];
                }
                const uint32_t base = acquire();
#pragma unroll
                for (int j = 0; j < 4; j++) {
#pragma unroll
                    for (int i = 0; i < 4; i++) {
                        uint32_t vf[4];
                        ldsm4t(vf, base + (voff ^ ((i >> 1) * 144 + (i & 1) * 2048)) + j * 8192);
                        mma16816(O[2 * ((i >> 1) ^ (i & 1)) + (i & 1)], vf, ps[i & 1][2 * j], ps[i & 1][2 * j + 1]);
                    }
                }
                release();
            }
        }
        uint32_t ow[2];
        float Z[2][4];
#pragma unroll
        for (int i = 0; i < 8; i++) Z[i >> 2][i & 3] = O[2 * (i >> 2)][i & 3] + O[2 * (i >> 2) + 1][i & 3];
#pragma unroll
        for (int mt = 0; mt < 2; mt++) {
            const float (&A)[4] = Z[mt];
            const float (&B)[4] = Z[mt ^ 1];
            const float lo = (t < 2 ? A[0] : B[1]) + __shfl_xor_sync(0xffffffffu, t < 2 ? A[1] : B[0], 2);
            const float hi = (t < 2 ? A[2] : B[3]) + __shfl_xor_sync(0xffffffffu, t < 2 ? A[3] : B[2], 2);
            ow[mt] = enc(pack_bf16(lo * fin, hi * fin));
        }
#pragma unroll
        for (int d = 0; d < 8; d++)
            asm volatile("st.relaxed.gpu.global.v2.u32 [%0], {%1,%2};" ::"l"(op + d * kHKV * 2048), "r"(ow[0]), "r"(ow[1]) : "memory");
        {
            uint32_t hf[7][4];
#pragma unroll
            for (int j = 0; j < 7; j++)
                ldsm4(hf[j], sb + SM_H + r7 * 512 + (2 * (j & 1) + (mi >> 1)) * 128 + (((2 * (j >> 1) + (mi & 1)) ^ r7) << 4));
            uint32_t wa2 = sb + SM_RING + (kW2N % kNSlot) * kSlot + (r7 + 8 * (mi >> 1)) * 128 + (((2 * w + (mi & 1)) ^ r7) << 4);
            uint32_t ya = mapa(sb + SM_Y + r * 256 + (16 * w + g) * 4, 2 * t), yb = mapa(bars + B_Y, 2 * t), wbar = bars + B_W2;
            const uint32_t ostep = mapa(bars + B_Y, 2 * t + 1) - yb;
            PIN(wa2); PIN(ya); PIN(yb); PIN(wbar);
            {
                mbar_wait(wbar, 0);
                float acc[4][4];
#pragma unroll
                for (int i = 0; i < 16; i++) acc[i >> 2][i & 3] = 0.f;
#pragma unroll
                for (int ks = 0; ks < 14; ks++) {
                    uint32_t af[4];
                    ldsm4t(af, wa2 + ks * 2048);
                    mma16816(acc[ks & 3], af, hf[ks >> 1][2 * (ks & 1)], hf[ks >> 1][2 * (ks & 1) + 1]);
                }
#pragma unroll
                for (int e = 0; e < 4; e++)
                    st_async(ya + (e & 1) * ostep + (e >> 1) * 32, __float_as_uint((acc[0][e] + acc[1][e]) + (acc[2][e] + acc[3][e])),
                             yb + (e & 1) * ostep);
            }
        }
    }
}

typedef CUresult (*EncodeFn)(CUtensorMap*, CUtensorMapDataType, cuuint32_t, void*, const cuuint64_t*, const cuuint64_t*,
                             const cuuint32_t*, const cuuint32_t*, CUtensorMapInterleave, CUtensorMapSwizzle,
                             CUtensorMapL2promotion, CUtensorMapFloatOOBfill);

void encode(EncodeFn fn, CUtensorMap* m, void* p, int rank, const cuuint64_t* dims, const cuuint64_t* strides,
            const cuuint32_t* box, CUtensorMapSwizzle sw = CU_TENSOR_MAP_SWIZZLE_128B) {
    const cuuint32_t es[4] = {1, 1, 1, 1};
    fn(m, CU_TENSOR_MAP_DATA_TYPE_BFLOAT16, rank, p, dims, strides, box, es, CU_TENSOR_MAP_INTERLEAVE_NONE,
       sw, CU_TENSOR_MAP_L2_PROMOTION_NONE, CU_TENSOR_MAP_FLOAT_OOB_FILL_NONE);
}

}

extern "C" void kernel_launch(void* const* d_in, const int* in_sizes, int n_in, void* d_out, int out_size) {
    (void)in_sizes; (void)n_in; (void)out_size;
    void* fnp = nullptr;
    cudaDriverEntryPointQueryResult qr;
    cudaGetDriverEntryPoint("cuTensorMapEncodeTiled", &fnp, cudaEnableDefault, &qr);
    EncodeFn fn = (EncodeFn)fnp;
    Params prm;
    {
        const cuuint64_t dims[3] = {64, 2, (cuuint64_t)8 * kHKV * kSK}, str[2] = {128, 256};
        const cuuint32_t box[3] = {64, 2, 128};
        encode(fn, &prm.m[0], d_in[1], 3, dims, str, box);
        encode(fn, &prm.m[1], d_in[2], 3, dims, str, box);
    }
    {
        const cuuint64_t dims[3] = {4096, 512, 1}, str[2] = {8192, 8192 * 512};
        const cuuint32_t box[3] = {64, 256, 1};
        encode(fn, &prm.m[2], d_in[3], 3, dims, str, box);
    }
    {
        const cuuint64_t dims[3] = {1792, 256, 2}, str[2] = {3584, 3584 * 256};
        const cuuint32_t box[3] = {32, 256, 2};
        encode(fn, &prm.m[3], d_in[6], 3, dims, str, box, CU_TENSOR_MAP_SWIZZLE_64B);
    }
    {
        const cuuint64_t dims[3] = {512, 1792, 1}, str[2] = {1024, 1024 * 1792};
        const cuuint32_t box[3] = {64, 224, 1};
        encode(fn, &prm.m[4], d_in[8], 3, dims, str, box);
    }
    {
        const cuuint64_t dims[4] = {512, 2, 8, 256}, str[3] = {8 * 1024, 1024, 16 * 1024};
        const cuuint32_t box[4] = {64, 2, 8, 8};
        encode(fn, &prm.m[5], d_in[4], 4, dims, str, box);
    }
    {
        int dev = 0, khz = 0, bits = 0;
        cudaGetDevice(&dev);
        cudaDeviceGetAttribute(&khz, cudaDevAttrMemoryClockRate, dev);
        cudaDeviceGetAttribute(&bits, cudaDevAttrGlobalMemoryBusWidth, dev);
        const double bytes_per_ns = 2.0 * khz * 1e-6 * bits / 8.0;
        const double scale = bytes_per_ns > 1000.0 ? (double)kGrid * kSlot / bytes_per_ns / kItemNs : 0.0;
        prm.sched_b = (int)(SCHED_B * scale + 0.5);
        prm.sched_a = (int)(SCHED_E * scale + 0.5) - (kItems - 1) * prm.sched_b;
    }
    cudaFuncSetAttribute(fused_decode_kernel, cudaFuncAttributeMaxDynamicSharedMemorySize, SM_BYTES);
    fused_decode_kernel<<<kGrid, kThreads, SM_BYTES>>>(
        (const __nv_bfloat16*)d_in[0], (const __nv_bfloat16*)d_in[7], (const __nv_bfloat16*)d_in[9],
        (__nv_bfloat16*)d_out, prm);
}
```

```cpp
#include <cuda_runtime.h>
#include <cuda_bf16.h>
#include <cuda.h>
#include <stdint.h>

namespace {

constexpr int kD = 512, kHKV = 8, kSK = 4096;
constexpr int kGrid = 64;
constexpr int kWarps = 14, kThreads = kWarps * 32;
constexpr int kSlot = 32768;
constexpr int kNSlot = 6;
constexpr int kItems = 70;
constexpr int kKVN = 3, kW2N = 67, kWoN = 68;
#define W_MAIN 4
#define LEAD 1
#define N_HEAD 6
#define HEAD_T0 900
#define HEAD_DT 550
#define SCHED_B 650
#define SCHED_E 43190
#define SCHED_D 360
#define SCHED_D2 275
#define OGATE_E 600
#define PFN 96
#define GO_N 40
constexpr int kWindow = W_MAIN, kWindowEnd = 3;
constexpr int kLead = LEAD;
constexpr int kGoN = GO_N;
constexpr int kHeadN = N_HEAD, kHeadT0 = HEAD_T0, kHeadDt = HEAD_DT;
constexpr int kGapW2 = SCHED_D, kGapWo = SCHED_D2, kGateO = OGATE_E - SCHED_D2;
constexpr double kItemNs = 625.6;
static_assert(kWindow >= 3 && kWindow < kNSlot && kNSlot <= 8 && kGoN < kKVN + 40, "ring");
static_assert(kWoN % kNSlot + 1 < kNSlot, "wo occupies two consecutive slots");

constexpr int kPStride = 2048 + 32;
constexpr int SM_RING = 0;
constexpr int SM_H = kNSlot * kSlot;
constexpr int SM_P = SM_H + 8 * 512;
constexpr int SM_X = SM_P + 4 * kPStride;
constexpr int SM_SCR = SM_X + 4 * kPStride;
constexpr int SM_Q = SM_SCR + 4 * 2176;
constexpr int SM_Y = SM_Q + 1024;
constexpr int SM_S = SM_Y + 2048;
constexpr int SM_ML = SM_S + 2048;
constexpr int SM_B1 = SM_ML + 64;
constexpr int SM_PROG = SM_B1 + 64;
constexpr int SM_BAR = SM_PROG + 32;
constexpr int B_FULL = 0, B_EMPTY = 8 * kNSlot, B_WO = 16 * kNSlot, B_W2 = B_WO + 32, B_GO = B_W2 + 8, B_GO2 = B_GO + 8,
              B_X = B_GO2 + 8, B_Q = B_X + 8, B_Y = B_Q + 8, B_S = B_Y + 8, B_H = B_S + 8, B_END = B_H + 8;
constexpr int SM_BYTES = SM_BAR + B_END;
static_assert(SM_BYTES <= 232448, "smem");

constexpr float kLog2e = 1.4426950408889634f;
constexpr uint32_t kSpinLimit = 1u << 22;
constexpr long long kWaitCycles = 1ll << 32;

struct Params {
    CUtensorMap m[6];
    int sched_a, sched_b;
};

__device__ __align__(128) uint32_t g_o[8][kHKV][2048];
__device__ __align__(128) uint32_t g_h[8][8][1024];

__device__ __forceinline__ uint32_t smem_u32(const void* p) { return (uint32_t)__cvta_generic_to_shared(p); }
__device__ __forceinline__ void mbar_init(uint32_t bar, uint32_t cnt) {
    asm volatile("mbarrier.init.shared::cta.b64 [%0], %1;" ::"r"(bar), "r"(cnt) : "memory");
}
__device__ __forceinline__ void mbar_expect_tx(uint32_t bar, uint32_t bytes) {
    asm volatile("mbarrier.arrive.expect_tx.shared::cta.b64 _, [%0], %1;" ::"r"(bar), "r"(bytes) : "memory");
}
__device__ __forceinline__ void mbar_arrive(uint32_t bar) {
    asm volatile("mbarrier.arrive.shared::cta.b64 _, [%0];" ::"r"(bar) : "memory");
}
__device__ __forceinline__ void mbar_arrive_n(uint32_t bar, uint32_t n) {
    asm volatile("mbarrier.arrive.shared::cta.b64 _, [%0], %1;" ::"r"(bar), "r"(n) : "memory");
}
__device__ __forceinline__ bool mbar_try(uint32_t bar, uint32_t parity) {
    uint32_t ok;
    asm volatile("{\n.reg .pred p;\nmbarrier.try_wait.parity.relaxed.cluster.shared::cta.b64 p, [%1], %2;\nselp.u32 %0, 1, 0, p;\n}"
                 : "=r"(ok) : "r"(bar), "r"(parity) : "memory");
    return ok != 0u;
}
__device__ __forceinline__ bool mbar_try_cta(uint32_t bar, uint32_t parity) {
    uint32_t ok;
    asm volatile("{\n.reg .pred p;\nmbarrier.try_wait.parity.shared::cta.b64 p, [%1], %2;\nselp.u32 %0, 1, 0, p;\n}"
                 : "=r"(ok) : "r"(bar), "r"(parity) : "memory");
    return ok != 0u;
}
__device__ __forceinline__ bool mbar_test(uint32_t bar, uint32_t parity) {
    uint32_t ok;
    asm volatile("{\n.reg .pred p;\nmbarrier.test_wait.parity.shared::cta.b64 p, [%1], %2;\nselp.u32 %0, 1, 0, p;\n}"
                 : "=r"(ok) : "r"(bar), "r"(parity) : "memory");
    return ok != 0u;
}
__device__ __forceinline__ void mbar_wait(uint32_t bar, uint32_t parity) {
    if (mbar_try_cta(bar, parity)) return;
    const long long t0 = clock64();
    while (!mbar_try_cta(bar, parity))
        if (clock64() - t0 > kWaitCycles) __trap();
}
__device__ __forceinline__ void mbar_wait_cl(uint32_t bar, uint32_t parity) {
    if (!mbar_try(bar, parity)) {
        const long long t0 = clock64();
        while (!mbar_try(bar, parity))
            if (clock64() - t0 > kWaitCycles) __trap();
    }
    asm volatile("fence.acquire.sync_restrict::shared::cluster.cluster;" ::: "memory");
}
#define PIN(x) asm volatile("shfl.sync.bfly.b32 %0, %0, 0, 0x1f, 0xffffffff;" : "+r"(x) :: "memory")
#define PINF(x) asm volatile("" : "+f"(x) :: "memory")
#define PINL(x) asm volatile("{\n.reg .b32 lo, hi;\nmov.b64 {lo, hi}, %0;\nshfl.sync.bfly.b32 lo, lo, 0, 0x1f, 0xffffffff;\n" \
                             "shfl.sync.bfly.b32 hi, hi, 0, 0x1f, 0xffffffff;\nmov.b64 %0, {lo, hi};\n}" : "+l"(x) :: "memory")
__device__ __forceinline__ void tma4d(uint32_t dst, const CUtensorMap* m, int c0, int c1, int c2, int c3, uint32_t bar) {
    asm volatile("cp.async.bulk.tensor.4d.shared::cluster.global.mbarrier::complete_tx::bytes [%0], [%1, {%3, %4, %5, %6}], [%2];"
                 ::"r"(dst), "l"(m), "r"(bar), "r"(c0), "r"(c1), "r"(c2), "r"(c3) : "memory");
}
__device__ __forceinline__ void tma3d(uint32_t dst, const CUtensorMap* m, int c0, int c1, int c2, uint32_t bar) {
    asm volatile("cp.async.bulk.tensor.3d.shared::cluster.global.mbarrier::complete_tx::bytes [%0], [%1, {%3, %4, %5}], [%2];"
                 ::"r"(dst), "l"(m), "r"(bar), "r"(c0), "r"(c1), "r"(c2) : "memory");
}
__device__ __forceinline__ void tma3d_hint(uint32_t dst, const CUtensorMap* m, int c0, int c1, int c2, uint32_t bar, uint64_t pol) {
    asm volatile("cp.async.bulk.tensor.3d.shared::cluster.global.mbarrier::complete_tx::bytes.L2::cache_hint [%0], [%1, {%3, %4, %5}], [%2], %6;"
                 ::"r"(dst), "l"(m), "r"(bar), "r"(c0), "r"(c1), "r"(c2), "l"(pol) : "memory");
}
__device__ __forceinline__ void bar_sync(int id, int n) { asm volatile("barrier.sync %0, %1;" ::"r"(id), "r"(n) : "memory"); }
__device__ __forceinline__ bool elect_one() {
    uint32_t p;
    asm volatile("{\n.reg .pred p;\nelect.sync _|p, 0xffffffff;\nselp.u32 %0, 1, 0, p;\n}" : "=r"(p));
    return p != 0u;
}
__device__ __forceinline__ void cluster_arrive() { asm volatile("barrier.cluster.arrive.relaxed;" ::: "memory"); }
__device__ __forceinline__ void cluster_wait() { asm volatile("barrier.cluster.wait;" ::: "memory"); }
__device__ __forceinline__ uint32_t mapa(uint32_t a, uint32_t rank) {
    uint32_t d;
    asm("mapa.shared::cluster.u32 %0, %1, %2;" : "=r"(d) : "r"(a), "r"(rank));
    return d;
}
__device__ __forceinline__ void st_async(uint32_t a, uint32_t v, uint32_t bar) {
    asm volatile("st.async.shared::cluster.mbarrier::complete_tx::bytes.u32 [%0], %1, [%2];" ::"r"(a), "r"(v), "r"(bar) : "memory");
}
__device__ __forceinline__ void st_async2_pred(uint32_t a, float x, float y, uint32_t bar, bool c) {
    asm volatile("{\n.reg .pred p;\nsetp.ne.u32 p, %4, 0;\n@p st.async.shared::cluster.mbarrier::complete_tx::bytes.v2.f32 [%0], {%1,%2}, [%3];\n}"
                 ::"r"(a), "f"(x), "f"(y), "r"(bar), "r"((uint32_t)c) : "memory");
}
__device__ __forceinline__ void st_async4(uint32_t a, uint32_t x, uint32_t y, uint32_t z, uint32_t w, uint32_t bar) {
    asm volatile("st.async.shared::cluster.mbarrier::complete_tx::bytes.v4.u32 [%0], {%1,%2,%3,%4}, [%5];"
                 ::"r"(a), "r"(x), "r"(y), "r"(z), "r"(w), "r"(bar) : "memory");
}

__device__ __forceinline__ void ldsm4(uint32_t (&r)[4], uint32_t a) {
    asm volatile("ldmatrix.sync.aligned.m8n8.x4.shared.b16 {%0,%1,%2,%3}, [%4];"
                 : "=r"(r[0]), "=r"(r[1]), "=r"(r[2]), "=r"(r[3]) : "r"(a) : "memory");
}
__device__ __forceinline__ void ldsm4t(uint32_t (&r)[4], uint32_t a) {
    asm volatile("ldmatrix.sync.aligned.m8n8.x4.trans.shared.b16 {%0,%1,%2,%3}, [%4];"
                 : "=r"(r[0]), "=r"(r[1]), "=r"(r[2]), "=r"(r[3]) : "r"(a) : "memory");
}
__device__ __forceinline__ void mma16816(float (&c)[4], const uint32_t (&a)[4], uint32_t b0, uint32_t b1) {
    asm volatile("mma.sync.aligned.m16n8k16.row.col.f32.bf16.bf16.f32 {%0,%1,%2,%3}, {%4,%5,%6,%7}, {%8,%9}, {%0,%1,%2,%3};"
                 : "+f"(c[0]), "+f"(c[1]), "+f"(c[2]), "+f"(c[3])
                 : "r"(a[0]), "r"(a[1]), "r"(a[2]), "r"(a[3]), "r"(b0), "r"(b1));
}
__device__ __forceinline__ uint32_t movm(uint32_t a) {
    uint32_t d;
    asm volatile("movmatrix.sync.aligned.m8n8.trans.b16 %0, %1;" : "=r"(d) : "r"(a));
    return d;
}
__device__ __forceinline__ uint32_t pack_bf16(float lo, float hi) {
    uint32_t d;
    asm("cvt.rn.bf16x2.f32 %0, %1, %2;" : "=r"(d) : "f"(hi), "f"(lo));
    return d;
}
__device__ __forceinline__ float bf_lo(uint32_t u) { return __uint_as_float(u << 16); }
__device__ __forceinline__ float bf_hi(uint32_t u) { return __uint_as_float(u & 0xffff0000u); }
__device__ __forceinline__ float bfr(float v) { return __uint_as_float(pack_bf16(0.f, v)); }
__device__ __forceinline__ uint32_t max_bf16x2(uint32_t a, uint32_t b) {
    uint32_t d;
    asm("max.bf16x2 %0, %1, %2;" : "=r"(d) : "r"(a), "r"(b));
    return d;
}
__device__ __forceinline__ float ex2(float x) {
    float y;
    asm("ex2.approx.ftz.f32 %0, %1;" : "=f"(y) : "f"(x));
    return y;
}
__device__ __forceinline__ float mul_sigmoid(float v, float z) { return __fdividef(v, 1.0f + ex2(fminf(-kLog2e * z, 120.f))); }
__device__ __forceinline__ uint32_t lds32(uint32_t a) { uint32_t v; asm volatile("ld.shared.u32 %0, [%1];" : "=r"(v) : "r"(a) : "memory"); return v; }
__device__ __forceinline__ float2 ldsf2(uint32_t a) { float2 v; asm volatile("ld.shared.v2.f32 {%0,%1}, [%2];" : "=f"(v.x), "=f"(v.y) : "r"(a) : "memory"); return v; }
__device__ __forceinline__ uint4 lds128(uint32_t a) {
    uint4 v;
    asm volatile("ld.shared.v4.u32 {%0,%1,%2,%3}, [%4];" : "=r"(v.x), "=r"(v.y), "=r"(v.z), "=r"(v.w) : "r"(a) : "memory");
    return v;
}
__device__ __forceinline__ void sts32(uint32_t a, uint32_t v) { asm volatile("st.shared.u32 [%0], %1;" ::"r"(a), "r"(v) : "memory"); }
__device__ __forceinline__ void stsf(uint32_t a, float v) { asm volatile("st.shared.f32 [%0], %1;" ::"r"(a), "f"(v) : "memory"); }
__device__ __forceinline__ void sts128(uint32_t a, uint32_t x, uint32_t y, uint32_t z, uint32_t w) {
    asm volatile("st.shared.v4.u32 [%0], {%1,%2,%3,%4};" ::"r"(a), "r"(x), "r"(y), "r"(z), "r"(w) : "memory");
}
__device__ __forceinline__ uint32_t enc(uint32_t b) { return b == 0u ? 0x80000000u : b; }
__device__ __forceinline__ void st_pred32(void* p, uint32_t v, bool c) {
    asm volatile("{\n.reg .pred p;\nsetp.ne.u32 p, %2, 0;\n@p st.global.u32 [%0], %1;\n}" ::"l"(p), "r"(v), "r"((uint32_t)c) : "memory");
}
__device__ __forceinline__ void ld_rlx4_pred(uint32_t (&v)[4], const uint32_t* p, bool c) {
    asm volatile("{\n.reg .pred p;\nsetp.ne.u32 p, %5, 0;\n@p ld.relaxed.gpu.global.v4.u32 {%0,%1,%2,%3}, [%4];\n}"
                 : "+r"(v[0]), "+r"(v[1]), "+r"(v[2]), "+r"(v[3]) : "l"(p), "r"((uint32_t)c) : "memory");
}
__device__ __forceinline__ uint32_t gt32() { uint32_t c; asm volatile("mov.u32 %0, %globaltimer_lo;" : "=r"(c) :: "memory"); return c; }
__device__ __forceinline__ void wait_until(uint32_t t0, int ns) {
    while (gt32() - t0 < (uint32_t)max(ns, 0)) {}
}
__device__ __forceinline__ uint32_t ldg32(const void* p) {
    uint32_t v;
    asm volatile("ld.global.nc.u32 %0, [%1];" : "=r"(v) : "l"(p));
    return v;
}

__global__ void __cluster_dims__(8, 1, 1) __launch_bounds__(kThreads, 1)
fused_decode_kernel(const __nv_bfloat16* __restrict__ x, const __nv_bfloat16* __restrict__ b1,
                    const __nv_bfloat16* __restrict__ b2, __nv_bfloat16* __restrict__ out, const char* __restrict__ kc,
                    const __grid_constant__ Params prm) {
    extern __shared__ __align__(1024) unsigned char smem_raw[];
    const uint32_t sb = smem_u32(smem_raw);
    const uint32_t bars = sb + SM_BAR;
    const int tid = threadIdx.x, wid = tid >> 5, lane = tid & 31;
    const int hkv = blockIdx.x >> 3, r = blockIdx.x & 7;
    asm volatile("{\n.reg .pred p;\nsetp.lt.u32 p, %1, %2;\n@p prefetch.global.L2 [%0];\n}"
                 ::"l"(kc + ((r * kHKV + hkv) * (kSK * 256u) + tid * 128u)), "r"(tid), "n"(PFN) : "memory");
    if (tid < 32) {
        if (elect_one()) {
            mbar_init(bars + B_FULL, 1);
            mbar_init(bars + B_FULL + 8, 1);
            asm volatile("fence.mbarrier_init.release.cluster;" ::: "memory");
#pragma unroll
            for (int n = 0; n < 2; n++) {
                mbar_expect_tx(bars + B_FULL + 8 * n, kSlot);
                tma3d(sb + SM_RING + n * kSlot, &prm.m[2], blockIdx.x * 64, n * 256, 0, bars + B_FULL + 8 * n);
            }
#pragma unroll
            for (int n = 2; n < kNSlot; n++) mbar_init(bars + B_FULL + 8 * n, 1);
            asm volatile("fence.mbarrier_init.release.cluster;" ::: "memory");
            mbar_expect_tx(bars + B_FULL + 16, r < 7 ? kSlot : 0);
            if (r < 7) tma3d(sb + SM_RING + 2 * kSlot, &prm.m[3], hkv * 224 + r * 32, 0, 0, bars + B_FULL + 16);
        }
    }
    const uint32_t t_start = gt32();
    if (wid == 1) asm volatile("prefetch.global.L1 [%0];" ::"l"(x + r * kD + lane * 16) : "memory");
    if (wid == 3 && lane < 4) asm volatile("prefetch.tensormap [%0];" ::"l"(&prm.m[lane + (lane & 2)]) : "memory");
    if (tid == 64) {
        if (sb & 1023u) __trap();
#pragma unroll
        for (int n = 0; n < kNSlot; n++) mbar_init(bars + B_EMPTY + 8 * n, 8);
#pragma unroll
        for (int n = B_WO; n < B_END; n += 8) mbar_init(bars + n, n < B_H ? 1 : 8);
        asm volatile("fence.mbarrier_init.release.cluster;" ::: "memory");
        sts128(sb + SM_PROG, 0, 0, 0, 0);
        sts128(sb + SM_PROG + 16, 0, 0, 0, 0);
        asm volatile("fence.release.sync_restrict::shared::cta.cluster;" ::: "memory");
        mbar_expect_tx(bars + B_X, 8192);
        mbar_expect_tx(bars + B_Q, 1024);
        mbar_expect_tx(bars + B_Y, 2048);
        mbar_expect_tx(bars + B_S, 2048);
    }
    __syncwarp();
    cluster_arrive();
    const int w = (wid - 2) & 7;
    const int g = lane >> 2, t = lane & 3, r7 = lane & 7, mi = lane >> 3;

    if (wid == 1) {
        {
            const uint4* xr = reinterpret_cast<const uint4*>(x + r * kD) + lane;
            const uint4 xv0 = __ldg(xr), xv1 = __ldg(xr + 32);
            float f[16];
            const uint32_t u[8] = {xv0.x, xv0.y, xv0.z, xv0.w, xv1.x, xv1.y, xv1.z, xv1.w};
#pragma unroll
            for (int i = 0; i < 8; i++) { f[2 * i] = bf_lo(u[i]); f[2 * i + 1] = bf_hi(u[i]); }
            float s = 0.f;
#pragma unroll
            for (int i = 0; i < 16; i++) s += f[i];
#pragma unroll
            for (int o = 16; o; o >>= 1) s += __shfl_xor_sync(0xffffffffu, s, o);
            const float mean = s * (1.0f / kD);
            float vs = 0.f;
#pragma unroll
            for (int i = 0; i < 16; i++) { const float d = f[i] - mean; vs = fmaf(d, d, vs); }
#pragma unroll
            for (int o = 16; o; o >>= 1) vs += __shfl_xor_sync(0xffffffffu, vs, o);
            const float mb = bfr(mean);
            const float den = bfr(__fsqrt_rn(bfr(bfr(vs * (1.0f / kD)) + 1e-5f)));
            const float rden = __frcp_rn(den);
            uint32_t q[8];
#pragma unroll
            for (int i = 0; i < 8; i++) {
                const uint32_t d2 = pack_bf16(f[2 * i] - mb, f[2 * i + 1] - mb);
                q[i] = pack_bf16(bf_lo(d2) * rden, bf_hi(d2) * rden);
            }
            const uint32_t xoff = SM_X + r * 1024 + ((lane >> 1) & 7) * 128 + (((2 * (lane >> 4) + (lane & 1)) ^ r) << 4);
            cluster_wait();
#pragma unroll 1
            for (int d = 0; d < 8; d++) {
                const uint32_t rb = mapa(sb, d), xa = rb + xoff;
                st_async4(xa, q[0], q[1], q[2], q[3], rb + SM_BAR + B_X);
                st_async4(xa ^ 64, q[4], q[5], q[6], q[7], rb + SM_BAR + B_X);
            }
        }
        const int col = hkv * 64 + 2 * lane;
        const uint32_t xw = ldg32(x + r * kD + col), bw = ldg32(b2 + col);
        __nv_bfloat16* dst = out + r * kD + col;
        uint32_t pa = sb + SM_Y + lane * 8, pbar = bars + B_Y;
        PINL(dst);
        float g0 = 0.f, g1 = 0.f;
#pragma unroll 1
        for (int pass = 0; pass < 2; pass++) {
            mbar_wait_cl(pbar, 0);
            float2 v[8];
#pragma unroll
            for (int c = 0; c < 8; c++) v[c] = ldsf2(pa + c * 256);
            const uint32_t sw = pack_bf16(((v[0].x + v[1].x) + (v[2].x + v[3].x)) + ((v[4].x + v[5].x) + (v[6].x + v[7].x)),
                                          ((v[0].y + v[1].y) + (v[2].y + v[3].y)) + ((v[4].y + v[5].y) + (v[6].y + v[7].y)));
            const uint32_t pw = pack_bf16(bf_lo(sw) * g0, bf_hi(sw) * g1);
            st_pred32(dst, pack_bf16(bf_lo(xw) + bf_lo(pw), bf_hi(xw) + bf_hi(pw)), pass);
            if (pass) break;
            const uint32_t yw = pack_bf16(bf_lo(sw) + bf_lo(bw), bf_hi(sw) + bf_hi(bw));
            const uint32_t gw = pack_bf16(mul_sigmoid(bf_lo(yw), bf_lo(yw)), mul_sigmoid(bf_hi(yw), bf_hi(yw)));
            g0 = bf_lo(gw);
            g1 = bf_hi(gw);
            pa = sb + SM_S + lane * 8;
            pbar = bars + B_S;
        }
    } else if (wid == 0) {
        cluster_wait();
        const int kvrow0 = (r * kHKV + hkv) * kSK;
        const uint32_t prog_remote = mapa(sb + SM_PROG + r * 4, lane & 7);
        uint64_t stream_pol;
        asm volatile("createpolicy.fractional.L2::evict_first.b64 %0, 1.0;" : "=l"(stream_pol));
        int slot = kKVN, ph = 0;
        int landed = 0, lslot = 0, lph = 0;
#pragma unroll 1
        for (int n = kKVN; n < kItems; n++) {
            if (n >= kNSlot) mbar_wait(bars + B_EMPTY + 8 * slot, ph ^ 1);
            for (const int need = n - (n >= kW2N ? kWindowEnd : kWindow); landed <= need; landed++) {
                mbar_wait(bars + B_FULL + 8 * lslot, lph);
                if (++lslot == kNSlot) { lslot = 0; lph ^= 1; }
            }
            wait_until(t_start, n < kHeadN ? kHeadT0 + (n - kKVN) * kHeadDt
                                           : prm.sched_a + n * prm.sched_b + (n < kW2N ? 0 : n < kWoN ? kGapW2 : kGapWo));
            if (n < kW2N) {
                if (lane < 8) asm volatile("st.relaxed.cluster.shared::cluster.u32 [%0], %1;" ::"r"(prog_remote), "r"(n) : "memory");
                for (uint32_t it = 0;; it++) {
                    int p;
                    asm volatile("ld.relaxed.cluster.shared::cta.u32 %0, [%1];" : "=r"(p) : "r"(sb + SM_PROG + (lane & 7) * 4) : "memory");
                    if (__all_sync(0xffffffffu, max(p, kKVN) + kLead >= n)) break;
                    if (it > kSpinLimit * 16) __trap();
                }
            }
            if (elect_one()) {
                const uint32_t dst = sb + SM_RING + slot * kSlot;
                if (n < kW2N) {
                    const int u = n - kKVN;
                    mbar_expect_tx(bars + B_FULL + 8 * slot, kSlot);
                    tma3d_hint(dst, &prm.m[(u >> 4) & 1], 0, 0, kvrow0 + (u >> 5) * 2048 + (u & 15) * 128, bars + B_FULL + 8 * slot, stream_pol);
                } else if (n >= kWoN) {
                    const uint32_t wb = bars + B_WO + 16 * (n - kWoN);
                    mbar_expect_tx(wb, kSlot / 2);
                    tma4d(dst, &prm.m[5], hkv * 64, 0, 0, r * 32 + (n - kWoN) * 16, wb);
                    mbar_expect_tx(wb + 8, kSlot / 2);
                    tma4d(dst + kSlot / 2, &prm.m[5], hkv * 64, 0, 0, r * 32 + (n - kWoN) * 16 + 8, wb + 8);
                } else {
                    mbar_expect_tx(bars + B_W2, 224 * 128);
                    tma3d(dst, &prm.m[4], hkv * 64, r * 224, 0, bars + B_W2);
                }
                if (n == kGoN) mbar_arrive(bars + B_GO);
            }
            __syncwarp();
            if (++slot == kNSlot) { slot = 0; ph ^= 1; }
        }
        wait_until(gt32(), kGateO);
        mbar_wait(bars + B_W2, 0);
        if (lane == 0) mbar_arrive(bars + B_GO2);
    } else if (wid < 10) {
        const int kg = w >> 1, ch = w & 1;
        if (w == 7 && lane < 16) sts32(sb + SM_B1 + lane * 4, ldg32(b1 + hkv * 224 + (r < 7 ? r : 0) * 32 + 2 * lane));
        uint32_t wa = sb + SM_SCR + kg * 2176 + t * 544 + (ch * 32 + g) * 4;
        uint32_t ra = sb + SM_SCR + w * 272 + lane * 8;
        uint32_t* op = &g_o[hkv][r][kg * 512 + lane * 4];
        const uint32_t baddr = sb + SM_X + r7 * 1024 + (mi & 1) * 512 + (((2 * kg + (mi >> 1)) ^ r7) << 4);
        uint32_t abase = sb + SM_RING + kg * (kSlot / 2) + (r7 + 64 * (mi >> 1)) * 128 + (((4 * ch + (mi & 1)) ^ r7) << 4);
        uint32_t abar = bars + B_FULL + 8 * (kg >> 1);
        uint32_t sa = mapa(sb + SM_S + r * 256 + lane * 8, w), sbar = mapa(bars + B_S, w);
        PIN(wa); PIN(ra); PINL(op); PIN(sa); PIN(sbar);
        uint32_t bf[4][4];
        auto fetch_o = [&]() {
            bool all = true;
#pragma unroll
            for (int j = 0; j < 4; j++) {
                const bool ok = bf[j][0] != 0u && bf[j][1] != 0u && bf[j][2] != 0u && bf[j][3] != 0u;
                all = all && ok;
                ld_rlx4_pred(bf[j], op + j * 128, !ok);
            }
            return __all_sync(0xffffffffu, all);
        };
        cluster_wait();
        mbar_wait_cl(bars + B_X, 0);
#pragma unroll 1
        for (int pass = 0; pass < 3; pass++) {
            float acc[2][2][4];
#pragma unroll
            for (int i = 0; i < 16; i++) acc[i >> 3][(i >> 2) & 1][i & 3] = 0.f;
            bool stream = true;
            if (pass == 2) {
                mbar_wait(bars + B_GO2, 0);
                for (uint32_t it = 0;; it++) {
                    stream = fetch_o();
                    if (stream || kg < 2 || __all_sync(0xffffffffu, mbar_test(abar, 0))) break;
                    if (it > kSpinLimit) __trap();
                }
            } else {
#pragma unroll
                for (int i = 0; i < 4; i++) ldsm4(bf[i], baddr + ((i + 2 * (pass & ch)) & 3) * 128);
            }
            if (pass == 1) {
                const uint32_t a1 = sb + SM_RING + 2 * kSlot + (128 * kg + 32 * ch + r7 + 64 * (mi >> 1)) * 64 + (((mi & 1) ^ (r7 >> 1)) << 4);
                mbar_wait(bars + B_FULL + 16, 0);
#pragma unroll
                for (int ks = 0; ks < 4; ks++) {
#pragma unroll
                    for (int mt = 0; mt < 2; mt++) {
                        uint32_t af[4];
                        ldsm4t(af, (a1 ^ (mt * 32)) + (ks >> 1) * 1024 + (ks & 1) * 512);
                        mma16816(acc[mt][ks & 1], af, bf[ks >> 1][2 * (ks & 1)], bf[ks >> 1][2 * (ks & 1) + 1]);
                    }
                }
            } else if (stream) {
                mbar_wait(abar, 0);
#pragma unroll
                for (int ks = 0; ks < 8; ks++) {
#pragma unroll
                    for (int mt = 0; mt < 2; mt++) {
                        uint32_t af[4];
                        ldsm4t(af, (abase ^ (mt * 32)) + ks * 1024);
                        mma16816(acc[mt][ks & 1], af, bf[ks >> 1][2 * (ks & 1)], bf[ks >> 1][2 * (ks & 1) + 1]);
                    }
                }
            } else {
                uint32_t af[8][2][4];
                mbar_wait(abar, 0);
#pragma unroll
                for (int ks = 0; ks < 8; ks++) {
                    ldsm4t(af[ks][0], abase + ks * 1024);
                    ldsm4t(af[ks][1], (abase ^ 32) + ks * 1024);
                }
                for (uint32_t it = 0; !fetch_o(); it++)
                    if (it > kSpinLimit) __trap();
#pragma unroll
                for (int ks = 0; ks < 8; ks++) {
                    mma16816(acc[0][ks & 1], af[ks][0], bf[ks >> 1][2 * (ks & 1)], bf[ks >> 1][2 * (ks & 1) + 1]);
                    mma16816(acc[1][ks & 1], af[ks][1], bf[ks >> 1][2 * (ks & 1)], bf[ks >> 1][2 * (ks & 1) + 1]);
                }
            }
#pragma unroll
            for (int mt = 0; mt < 2; mt++) {
#pragma unroll
                for (int e = 0; e < 4; e++)
                    stsf(wa + (e & 1) * 272 + (mt * 16 + 8 * (e >> 1)) * 4, acc[mt][0][e] + acc[mt][1][e]);
            }
            bar_sync(1, 256);
            const float2 p0 = ldsf2(ra), p1 = ldsf2(ra + 2176), p2 = ldsf2(ra + 2 * 2176), p3 = ldsf2(ra + 3 * 2176);
            float s0 = (p0.x + p1.x) + (p2.x + p3.x), s1 = (p0.y + p1.y) + (p2.y + p3.y);
            st_async2_pred(sa, s0, s1, sbar, pass == 2);
            if (pass == 2) break;
            if (pass == 0) {
                const uint32_t rb = mapa(sb, w);
                st_async(rb + SM_Q + (r * 32 + lane) * 4, pack_bf16(s0, s1), rb + SM_BAR + B_Q);
                if (lane == 0) mbar_arrive_n(bars + B_EMPTY + 8 * (kg >> 1), 2);
            } else {
                if (lane == 0) mbar_arrive(bars + B_EMPTY + 16);
                s0 += __shfl_xor_sync(0xffffffffu, s0, 16);
                s1 += __shfl_xor_sync(0xffffffffu, s1, 16);
                const uint32_t sw = pack_bf16(s0, s1), b1w = lds32(sb + SM_B1 + (lane & 15) * 4);
                const uint32_t vw = pack_bf16(bf_lo(sw) + bf_lo(b1w), bf_hi(sw) + bf_hi(b1w));
                const float v0 = bf_lo(vw), v1 = bf_hi(vw);
                const float c = 2.0f * 0.7978845608028654f;
                uint32_t hw = pack_bf16(mul_sigmoid(v0, c * (v0 + 0.044715f * v0 * v0 * v0)),
                                        mul_sigmoid(v1, c * (v1 + 0.044715f * v1 * v1 * v1)));
                hw = r < 7 ? enc(hw) : 0x80000000u;
                {
                    uint32_t* cp = &g_o[w][hkv][(g * 16 + r) * 16 + t * 4];
                    *reinterpret_cast<uint4*>(cp) = make_uint4(0u, 0u, 0u, 0u);
                    *reinterpret_cast<uint4*>(cp + 128) = make_uint4(0u, 0u, 0u, 0u);
                    __threadfence();
                    bar_sync(1, 256);
                }
                {
                    uint32_t* hp = &g_h[(lane >> 4) * 4][hkv][w * 128 + (2 * (r & 1) + (mi & 1)) * 32 + (((2 * (r >> 1) + (r7 >> 2)) ^ w) << 2) + t];
#pragma unroll
                    for (int d = 0; d < 4; d++) asm volatile("st.relaxed.gpu.global.u32 [%0], %1;" ::"l"(hp + d * 8 * 1024), "r"(hw) : "memory");
                }
                mbar_wait(bars + B_GO, 0);
                {
                    uint32_t* hp = &g_h[hkv][r][w * 128 + lane * 4];
                    uint4 v;
                    for (uint32_t it = 0;; it++) {
                        asm volatile("ld.relaxed.gpu.global.v4.u32 {%0,%1,%2,%3}, [%4];" : "=r"(v.x), "=r"(v.y), "=r"(v.z), "=r"(v.w) : "l"(hp) : "memory");
                        if (v.x != 0u && v.y != 0u && v.z != 0u && v.w != 0u) break;
                        if (it > kSpinLimit) __trap();
                    }
                    sts128(sb + SM_H + w * 512 + lane * 16, v.x, v.y, v.z, v.w);
                    *reinterpret_cast<uint4*>(hp) = make_uint4(0u, 0u, 0u, 0u);
                    __threadfence();
                }
                __syncwarp();
                if (lane == 0) mbar_arrive(bars + B_H);
#pragma unroll
                for (int i = 0; i < 16; i++) bf[i >> 2][i & 3] = 0u;
                abase += (kWoN % kNSlot) * kSlot;
                abar = bars + B_WO + 8 * kg;
                PIN(abase); PIN(abar);
            }
            bar_sync(1, 256);
        }
    } else {
        int slot = kKVN, ph = 0;
        auto acquire = [&]() {
            mbar_wait(bars + B_FULL + 8 * slot, ph);
            return sb + SM_RING + slot * kSlot;
        };
        auto release = [&]() {
            __syncwarp();
            if (lane == 0) mbar_arrive_n(bars + B_EMPTY + 8 * slot, 2);
            if (++slot == kNSlot) { slot = 0; ph ^= 1; }
        };
        const int hl = r7 >> 2;
        const bool diag = (g >> 2) == (t >> 1);
        uint32_t koff[4];
#pragma unroll
        for (int c = 0; c < 4; c++)
            koff[c] = (w * 32 + r7 + 8 * (mi & 1)) * 256 + hl * 128 + (((2 * c + (mi >> 1)) ^ (2 * (r7 & 3) + hl)) << 4);
        const uint32_t voff = (16 * (mi >> 1) + r7 + 8 * hl) * 256 + hl * 128 + (((2 * w + (mi & 1)) ^ (2 * (r7 & 3) + hl)) << 4);
        const int ht = 2 * (t & 1) + (t >> 1);
        uint32_t* op = &g_o[0][hkv][((ht * 4 + w) * 8 + r) * 16 + (g & 3) * 4 + 2 * (g >> 2)];
        PINL(op);
        cluster_wait();
        uint32_t qf[8][2];
        mbar_wait_cl(bars + B_Q, 0);
#pragma unroll
        for (int ks = 0; ks < 8; ks++) {
            qf[ks][0] = lds32(sb + SM_Q + ((g & 3) * 64 + (ks ^ (g & 4)) * 8 + t) * 4);
            qf[ks][1] = lds32(sb + SM_Q + ((g & 3) * 64 + (ks ^ (g & 4)) * 8 + 4 + t) * 4);
        }
        uint32_t mx2 = 0xff7fff7fu;
        uint32_t mprev = 0xff7fff7fu;
        float Mw = bf_hi(mprev), l = 0.f, fin = 0.f;
        float O[4][4];
#pragma unroll
        for (int i = 0; i < 4; i++) { O[i][0] = O[i][1] = O[i][2] = O[i][3] = 0.f; }
#pragma unroll 1
        for (int c = 0; c < 2; c++) {
            uint32_t pa = sb + SM_P + (g & 3) * kPStride + (diag ? 0 : 16) + t * 4 + w * 64;
#pragma unroll 1
            for (int it = 0; it < 16; it++) {
                const uint32_t base = acquire();
                float sc[2][2][4];
#pragma unroll
                for (int i = 0; i < 16; i++) sc[i >> 3][(i >> 2) & 1][i & 3] = 0.f;
#pragma unroll
                for (int ks = 0; ks < 8; ks++) {
#pragma unroll
                    for (int mt = 0; mt < 2; mt++) {
                        uint32_t kf[4];
                        ldsm4(kf, base + (koff[ks & 3] ^ ((ks >> 2) * 144)) + mt * 4096);
                        mma16816(sc[mt][ks & 1], kf, qf[ks][0], qf[ks][1]);
                    }
                }
                release();
#pragma unroll
                for (int mt = 0; mt < 2; mt++) {
                    const uint32_t sa = pack_bf16(sc[mt][0][0] + sc[mt][1][0], sc[mt][0][1] + sc[mt][1][1]);
                    const uint32_t sx = __shfl_xor_sync(0xffffffffu, pack_bf16(sc[mt][0][2] + sc[mt][1][2], sc[mt][0][3] + sc[mt][1][3]), 2);
                    const uint32_t s2 = diag ? sa : sx;
                    const float scale = 0.08838834764831845f;
                    const uint32_t v = pack_bf16(bf_lo(s2) * scale, bf_hi(s2) * scale);
                    mx2 = max_bf16x2(mx2, v);
                    sts32(pa + mt * 32, movm(v));
                }
                pa += it == 7 ? 4 * kPStride - 7 * 256 : 256;
            }
            {
#pragma unroll
                for (int o = 2; o <= 16; o <<= 1) mx2 = max_bf16x2(mx2, __shfl_xor_sync(0xffffffffu, mx2, o));
                if (lane < 2) sts32(sb + SM_ML + lane * 16 + w * 4, mx2);
                bar_sync(2, 128);
                const uint4 a0 = lds128(sb + SM_ML), b0 = lds128(sb + SM_ML + 16);
                const uint32_t m01 = max_bf16x2(max_bf16x2(a0.x, a0.y), max_bf16x2(a0.z, a0.w));
                const uint32_t m23 = max_bf16x2(max_bf16x2(b0.x, b0.y), max_bf16x2(b0.z, b0.w));
                const uint32_t mw = (w & 2) ? m23 : m01, mt = (t & 1) ? m23 : m01;
                const float M = (w & 1) ? bf_hi(mw) : bf_lo(mw);
                l *= ex2((Mw - M) * kLog2e);
                Mw = M;
                const float al0 = ex2((bf_lo(mprev) - bf_lo(mt)) * kLog2e), al1 = ex2((bf_hi(mprev) - bf_hi(mt)) * kLog2e);
                mprev = mt;
#pragma unroll
                for (int i = 0; i < 4; i++) { O[i][0] *= al0; O[i][1] *= al1; O[i][2] *= al0; O[i][3] *= al1; }
                const uint32_t ea = sb + SM_P + w * kPStride + lane * 16;
#pragma unroll 2
                for (int i = 0; i < 8; i++) {
                    const uint32_t ei = ea + (i >> 2) * (4 * kPStride) + (i & 3) * 512;
                    const uint4 sv = lds128(ei);
                    const uint32_t uu[4] = {sv.x, sv.y, sv.z, sv.w};
                    uint32_t rr[4];
#pragma unroll
                    for (int e = 0; e < 4; e++) {
                        const float p0 = ex2((bf_lo(uu[e]) - M) * kLog2e), p1 = ex2((bf_hi(uu[e]) - M) * kLog2e);
                        l += p0 + p1;
                        rr[e] = pack_bf16(p0, p1);
                    }
                    sts128(ei, rr[0], rr[1], rr[2], rr[3]);
                }
                float ls = l;
#pragma unroll
                for (int o = 16; o; o >>= 1) ls += __shfl_xor_sync(0xffffffffu, ls, o);
                if (lane == 0) stsf(sb + SM_ML + 32 + w * 4, ls);
                bar_sync(2, 128);
                fin = __fdividef(1.0f, __uint_as_float(lds32(sb + SM_ML + 32 + ht * 4)));
                PINF(fin);
                if (c == 1) mbar_wait(bars + B_H, 0);
            }
            pa = sb + SM_P + (r7 & 3) * kPStride + (r7 >> 2) * 16 + mi * 32;
#pragma unroll 1
            for (int it = 0; it < 16; it++) {
                uint32_t pf[2][4], ps[2][8];
                ldsm4(pf[0], pa);
                ldsm4(pf[1], pa + 128);
                pa += it == 7 ? 4 * kPStride - 7 * 256 : 256;
#pragma unroll
                for (int i = 0; i < 8; i++) {
                    ps[0][i] = diag ? pf[i >> 2][i & 3] : 0u;
                    ps[1][i] = diag ? 0u : pf[i >> 2][i & 3];
                }
                const uint32_t base = acquire();
#pragma unroll
                for (int j = 0; j < 4; j++) {
#pragma unroll
                    for (int i = 0; i < 4; i++) {
                        uint32_t vf[4];
                        ldsm4t(vf, base + (voff ^ ((i >> 1) * 144 + (i & 1) * 2048)) + j * 8192);
                        mma16816(O[2 * ((i >> 1) ^ (i & 1)) + (i & 1)], vf, ps[i & 1][2 * j], ps[i & 1][2 * j + 1]);
                    }
                }
                release();
            }
        }
        uint32_t ow[2];
        float Z[2][4];
#pragma unroll
        for (int i = 0; i < 8; i++) Z[i >> 2][i & 3] = O[2 * (i >> 2)][i & 3] + O[2 * (i >> 2) + 1][i & 3];
#pragma unroll
        for (int mt = 0; mt < 2; mt++) {
            const float (&A)[4] = Z[mt];
            const float (&B)[4] = Z[mt ^ 1];
            const float lo = (t < 2 ? A[0] : B[1]) + __shfl_xor_sync(0xffffffffu, t < 2 ? A[1] : B[0], 2);
            const float hi = (t < 2 ? A[2] : B[3]) + __shfl_xor_sync(0xffffffffu, t < 2 ? A[3] : B[2], 2);
            ow[mt] = enc(pack_bf16(lo * fin, hi * fin));
        }
#pragma unroll
        for (int d = 0; d < 8; d++)
            asm volatile("st.relaxed.gpu.global.v2.u32 [%0], {%1,%2};" ::"l"(op + d * kHKV * 2048), "r"(ow[0]), "r"(ow[1]) : "memory");
        {
            uint32_t hf[7][4];
#pragma unroll
            for (int j = 0; j < 7; j++)
                ldsm4(hf[j], sb + SM_H + r7 * 512 + (2 * (j & 1) + (mi >> 1)) * 128 + (((2 * (j >> 1) + (mi & 1)) ^ r7) << 4));
            uint32_t wa2 = sb + SM_RING + (kW2N % kNSlot) * kSlot + (r7 + 8 * (mi >> 1)) * 128 + (((2 * w + (mi & 1)) ^ r7) << 4);
            uint32_t ya = mapa(sb + SM_Y + r * 256 + (16 * w + g) * 4, 2 * t), yb = mapa(bars + B_Y, 2 * t), wbar = bars + B_W2;
            const uint32_t ostep = mapa(bars + B_Y, 2 * t + 1) - yb;
            PIN(wa2); PIN(ya); PIN(yb); PIN(wbar);
            {
                mbar_wait(wbar, 0);
                float acc[4][4];
#pragma unroll
                for (int i = 0; i < 16; i++) acc[i >> 2][i & 3] = 0.f;
#pragma unroll
                for (int ks = 0; ks < 14; ks++) {
                    uint32_t af[4];
                    ldsm4t(af, wa2 + ks * 2048);
                    mma16816(acc[ks & 3], af, hf[ks >> 1][2 * (ks & 1)], hf[ks >> 1][2 * (ks & 1) + 1]);
                }
#pragma unroll
                for (int e = 0; e < 4; e++)
                    st_async(ya + (e & 1) * ostep + (e >> 1) * 32, __float_as_uint((acc[0][e] + acc[1][e]) + (acc[2][e] + acc[3][e])),
                             yb + (e & 1) * ostep);
            }
        }
    }
}

typedef CUresult (*EncodeFn)(CUtensorMap*, CUtensorMapDataType, cuuint32_t, void*, const cuuint64_t*, const cuuint64_t*,
                             const cuuint32_t*, const cuuint32_t*, CUtensorMapInterleave, CUtensorMapSwizzle,
                             CUtensorMapL2promotion, CUtensorMapFloatOOBfill);

void encode(EncodeFn fn, CUtensorMap* m, void* p, int rank, const cuuint64_t* dims, const cuuint64_t* strides,
            const cuuint32_t* box, CUtensorMapSwizzle sw = CU_TENSOR_MAP_SWIZZLE_128B) {
    const cuuint32_t es[4] = {1, 1, 1, 1};
    fn(m, CU_TENSOR_MAP_DATA_TYPE_BFLOAT16, rank, p, dims, strides, box, es, CU_TENSOR_MAP_INTERLEAVE_NONE,
       sw, CU_TENSOR_MAP_L2_PROMOTION_NONE, CU_TENSOR_MAP_FLOAT_OOB_FILL_NONE);
}

}

extern "C" void kernel_launch(void* const* d_in, const int* in_sizes, int n_in, void* d_out, int out_size) {
    (void)in_sizes; (void)n_in; (void)out_size;
    void* fnp = nullptr;
    cudaDriverEntryPointQueryResult qr;
    cudaGetDriverEntryPoint("cuTensorMapEncodeTiled", &fnp, cudaEnableDefault, &qr);
    EncodeFn fn = (EncodeFn)fnp;
    Params prm;
    {
        const cuuint64_t dims[3] = {64, 2, (cuuint64_t)8 * kHKV * kSK}, str[2] = {128, 256};
        const cuuint32_t box[3] = {64, 2, 128};
        encode(fn, &prm.m[0], d_in[1], 3, dims, str, box);
        encode(fn, &prm.m[1], d_in[2], 3, dims, str, box);
    }
    {
        const cuuint64_t dims[3] = {4096, 512, 1}, str[2] = {8192, 8192 * 512};
        const cuuint32_t box[3] = {64, 256, 1};
        encode(fn, &prm.m[2], d_in[3], 3, dims, str, box);
    }
    {
        const cuuint64_t dims[3] = {1792, 256, 2}, str[2] = {3584, 3584 * 256};
        const cuuint32_t box[3] = {32, 256, 2};
        encode(fn, &prm.m[3], d_in[6], 3, dims, str, box, CU_TENSOR_MAP_SWIZZLE_64B);
    }
    {
        const cuuint64_t dims[3] = {512, 1792, 1}, str[2] = {1024, 1024 * 1792};
        const cuuint32_t box[3] = {64, 224, 1};
        encode(fn, &prm.m[4], d_in[8], 3, dims, str, box);
    }
    {
        const cuuint64_t dims[4] = {512, 2, 8, 256}, str[3] = {8 * 1024, 1024, 16 * 1024};
        const cuuint32_t box[4] = {64, 2, 8, 8};
        encode(fn, &prm.m[5], d_in[4], 4, dims, str, box);
    }
    {
        int dev = 0, khz = 0, bits = 0;
        cudaGetDevice(&dev);
        cudaDeviceGetAttribute(&khz, cudaDevAttrMemoryClockRate, dev);
        cudaDeviceGetAttribute(&bits, cudaDevAttrGlobalMemoryBusWidth, dev);
        const double bytes_per_ns = 2.0 * khz * 1e-6 * bits / 8.0;
        const double scale = bytes_per_ns > 1000.0 ? (double)kGrid * kSlot / bytes_per_ns / kItemNs : 0.0;
        prm.sched_b = (int)(SCHED_B * scale + 0.5);
        prm.sched_a = (int)(SCHED_E * scale + 0.5) - (kItems - 1) * prm.sched_b;
    }
    cudaFuncSetAttribute(fused_decode_kernel, cudaFuncAttributeMaxDynamicSharedMemorySize, SM_BYTES);
    fused_decode_kernel<<<kGrid, kThreads, SM_BYTES>>>(
        (const __nv_bfloat16*)d_in[0], (const __nv_bfloat16*)d_in[7], (const __nv_bfloat16*)d_in[9],
        (__nv_bfloat16*)d_out, (const char*)d_in[1], prm);
}
```

```cpp
#include <cuda_runtime.h>
#include <cuda_bf16.h>
#include <cuda.h>
#include <stdint.h>

namespace {

constexpr int kD = 512, kHKV = 8, kSK = 4096;
constexpr int kGrid = 64;
constexpr int kWarps = 14, kThreads = kWarps * 32;
constexpr int kSlot = 32768;
constexpr int kNSlot = 6;
constexpr int kItems = 70;
constexpr int kKVN = 3, kW2N = 67, kWoN = 68;
#define W_MAIN 4
#define LEAD 1
#define N_HEAD 6
#define HEAD_T0 900
#define HEAD_DT 550
#define SCHED_B 650
#define SCHED_E 43200
#define SCHED_D 360
#define SCHED_D2 275
#define OGATE_E 600
#define PFN 96
#define GO_N 40
constexpr int kWindow = W_MAIN, kWindowEnd = 3;
constexpr int kLead = LEAD;
constexpr int kGoN = GO_N;
constexpr int kHeadN = N_HEAD, kHeadT0 = HEAD_T0, kHeadDt = HEAD_DT;
constexpr int kGapW2 = SCHED_D, kGapWo = SCHED_D2, kGateO = OGATE_E - SCHED_D2;
constexpr double kItemNs = 625.6;
static_assert(kWindow >= 3 && kWindow < kNSlot && kNSlot <= 8 && kGoN < kKVN + 40, "ring");
static_assert(kWoN % kNSlot + 1 < kNSlot, "wo occupies two consecutive slots");

constexpr int kPStride = 2048 + 32;
constexpr int SM_RING = 0;
constexpr int SM_H = kNSlot * kSlot;
constexpr int SM_P = SM_H + 8 * 512;
constexpr int SM_X = SM_P + 4 * kPStride;
constexpr int SM_SCR = SM_X + 4 * kPStride;
constexpr int SM_Q = SM_SCR + 4 * 2176;
constexpr int SM_Y = SM_Q + 1024;
constexpr int SM_S = SM_Y + 2048;
constexpr int SM_ML = SM_S + 2048;
constexpr int SM_B1 = SM_ML + 64;
constexpr int SM_PROG = SM_B1 + 64;
constexpr int SM_BAR = SM_PROG + 32;
constexpr int B_FULL = 0, B_EMPTY = 8 * kNSlot, B_WO = 16 * kNSlot, B_W2 = B_WO + 32, B_GO = B_W2 + 8, B_GO2 = B_GO + 8,
              B_X = B_GO2 + 8, B_Q = B_X + 8, B_Y = B_Q + 8, B_S = B_Y + 8, B_H = B_S + 8, B_END = B_H + 8;
constexpr int SM_BYTES = SM_BAR + B_END;
static_assert(SM_BYTES <= 232448, "smem");

constexpr float kLog2e = 1.4426950408889634f;
constexpr uint32_t kSpinLimit = 1u << 22;
constexpr long long kWaitCycles = 1ll << 32;

struct Params {
    CUtensorMap m[6];
    int sched_a, sched_b;
};

__device__ __align__(128) uint32_t g_o[8][kHKV][2048];
__device__ __align__(128) uint32_t g_h[8][8][1024];

__device__ __forceinline__ uint32_t smem_u32(const void* p) { return (uint32_t)__cvta_generic_to_shared(p); }
__device__ __forceinline__ void mbar_init(uint32_t bar, uint32_t cnt) {
    asm volatile("mbarrier.init.shared::cta.b64 [%0], %1;" ::"r"(bar), "r"(cnt) : "memory");
}
__device__ __forceinline__ void mbar_expect_tx(uint32_t bar, uint32_t bytes) {
    asm volatile("mbarrier.arrive.expect_tx.shared::cta.b64 _, [%0], %1;" ::"r"(bar), "r"(bytes) : "memory");
}
__device__ __forceinline__ void mbar_arrive(uint32_t bar) {
    asm volatile("mbarrier.arrive.shared::cta.b64 _, [%0];" ::"r"(bar) : "memory");
}
__device__ __forceinline__ void mbar_arrive_n(uint32_t bar, uint32_t n) {
    asm volatile("mbarrier.arrive.shared::cta.b64 _, [%0], %1;" ::"r"(bar), "r"(n) : "memory");
}
__device__ __forceinline__ bool mbar_try(uint32_t bar, uint32_t parity) {
    uint32_t ok;
    asm volatile("{\n.reg .pred p;\nmbarrier.try_wait.parity.relaxed.cluster.shared::cta.b64 p, [%1], %2;\nselp.u32 %0, 1, 0, p;\n}"
                 : "=r"(ok) : "r"(bar), "r"(parity) : "memory");
    return ok != 0u;
}
__device__ __forceinline__ bool mbar_try_cta(uint32_t bar, uint32_t parity) {
    uint32_t ok;
    asm volatile("{\n.reg .pred p;\nmbarrier.try_wait.parity.shared::cta.b64 p, [%1], %2;\nselp.u32 %0, 1, 0, p;\n}"
                 : "=r"(ok) : "r"(bar), "r"(parity) : "memory");
    return ok != 0u;
}
__device__ __forceinline__ bool mbar_test(uint32_t bar, uint32_t parity) {
    uint32_t ok;
    asm volatile("{\n.reg .pred p;\nmbarrier.test_wait.parity.shared::cta.b64 p, [%1], %2;\nselp.u32 %0, 1, 0, p;\n}"
                 : "=r"(ok) : "r"(bar), "r"(parity) : "memory");
    return ok != 0u;
}
__device__ __forceinline__ void mbar_wait(uint32_t bar, uint32_t parity) {
    if (mbar_try_cta(bar, parity)) return;
    const long long t0 = clock64();
    while (!mbar_try_cta(bar, parity))
        if (clock64() - t0 > kWaitCycles) __trap();
}
__device__ __forceinline__ void mbar_wait_cl(uint32_t bar, uint32_t parity) {
    if (!mbar_try(bar, parity)) {
        const long long t0 = clock64();
        while (!mbar_try(bar, parity))
            if (clock64() - t0 > kWaitCycles) __trap();
    }
    asm volatile("fence.acquire.sync_restrict::shared::cluster.cluster;" ::: "memory");
}
#define PIN(x) asm volatile("shfl.sync.bfly.b32 %0, %0, 0, 0x1f, 0xffffffff;" : "+r"(x) :: "memory")
#define PINF(x) asm volatile("" : "+f"(x) :: "memory")
#define PINL(x) asm volatile("{\n.reg .b32 lo, hi;\nmov.b64 {lo, hi}, %0;\nshfl.sync.bfly.b32 lo, lo, 0, 0x1f, 0xffffffff;\n" \
                             "shfl.sync.bfly.b32 hi, hi, 0, 0x1f, 0xffffffff;\nmov.b64 %0, {lo, hi};\n}" : "+l"(x) :: "memory")
__device__ __forceinline__ void tma4d(uint32_t dst, const CUtensorMap* m, int c0, int c1, int c2, int c3, uint32_t bar) {
    asm volatile("cp.async.bulk.tensor.4d.shared::cluster.global.mbarrier::complete_tx::bytes [%0], [%1, {%3, %4, %5, %6}], [%2];"
                 ::"r"(dst), "l"(m), "r"(bar), "r"(c0), "r"(c1), "r"(c2), "r"(c3) : "memory");
}
__device__ __forceinline__ void tma3d(uint32_t dst, const CUtensorMap* m, int c0, int c1, int c2, uint32_t bar) {
    asm volatile("cp.async.bulk.tensor.3d.shared::cluster.global.mbarrier::complete_tx::bytes [%0], [%1, {%3, %4, %5}], [%2];"
                 ::"r"(dst), "l"(m), "r"(bar), "r"(c0), "r"(c1), "r"(c2) : "memory");
}
__device__ __forceinline__ void tma3d_hint(uint32_t dst, const CUtensorMap* m, int c0, int c1, int c2, uint32_t bar, uint64_t pol) {
    asm volatile("cp.async.bulk.tensor.3d.shared::cluster.global.mbarrier::complete_tx::bytes.L2::cache_hint [%0], [%1, {%3, %4, %5}], [%2], %6;"
                 ::"r"(dst), "l"(m), "r"(bar), "r"(c0), "r"(c1), "r"(c2), "l"(pol) : "memory");
}
__device__ __forceinline__ void bar_sync(int id, int n) { asm volatile("barrier.sync %0, %1;" ::"r"(id), "r"(n) : "memory"); }
__device__ __forceinline__ bool elect_one() {
    uint32_t p;
    asm volatile("{\n.reg .pred p;\nelect.sync _|p, 0xffffffff;\nselp.u32 %0, 1, 0, p;\n}" : "=r"(p));
    return p != 0u;
}
__device__ __forceinline__ void cluster_arrive() { asm volatile("barrier.cluster.arrive.relaxed;" ::: "memory"); }
__device__ __forceinline__ void cluster_wait() { asm volatile("barrier.cluster.wait;" ::: "memory"); }
__device__ __forceinline__ uint32_t mapa(uint32_t a, uint32_t rank) {
    uint32_t d;
    asm("mapa.shared::cluster.u32 %0, %1, %2;" : "=r"(d) : "r"(a), "r"(rank));
    return d;
}
__device__ __forceinline__ void st_async(uint32_t a, uint32_t v, uint32_t bar) {
    asm volatile("st.async.shared::cluster.mbarrier::complete_tx::bytes.u32 [%0], %1, [%2];" ::"r"(a), "r"(v), "r"(bar) : "memory");
}
__device__ __forceinline__ void st_async2_pred(uint32_t a, float x, float y, uint32_t bar, bool c) {
    asm volatile("{\n.reg .pred p;\nsetp.ne.u32 p, %4, 0;\n@p st.async.shared::cluster.mbarrier::complete_tx::bytes.v2.f32 [%0], {%1,%2}, [%3];\n}"
                 ::"r"(a), "f"(x), "f"(y), "r"(bar), "r"((uint32_t)c) : "memory");
}
__device__ __forceinline__ void st_async4(uint32_t a, uint32_t x, uint32_t y, uint32_t z, uint32_t w, uint32_t bar) {
    asm volatile("st.async.shared::cluster.mbarrier::complete_tx::bytes.v4.u32 [%0], {%1,%2,%3,%4}, [%5];"
                 ::"r"(a), "r"(x), "r"(y), "r"(z), "r"(w), "r"(bar) : "memory");
}

__device__ __forceinline__ void ldsm4(uint32_t (&r)[4], uint32_t a) {
    asm volatile("ldmatrix.sync.aligned.m8n8.x4.shared.b16 {%0,%1,%2,%3}, [%4];"
                 : "=r"(r[0]), "=r"(r[1]), "=r"(r[2]), "=r"(r[3]) : "r"(a) : "memory");
}
__device__ __forceinline__ void ldsm4t(uint32_t (&r)[4], uint32_t a) {
    asm volatile("ldmatrix.sync.aligned.m8n8.x4.trans.shared.b16 {%0,%1,%2,%3}, [%4];"
                 : "=r"(r[0]), "=r"(r[1]), "=r"(r[2]), "=r"(r[3]) : "r"(a) : "memory");
}
__device__ __forceinline__ void mma16816(float (&c)[4], const uint32_t (&a)[4], uint32_t b0, uint32_t b1) {
    asm volatile("mma.sync.aligned.m16n8k16.row.col.f32.bf16.bf16.f32 {%0,%1,%2,%3}, {%4,%5,%6,%7}, {%8,%9}, {%0,%1,%2,%3};"
                 : "+f"(c[0]), "+f"(c[1]), "+f"(c[2]), "+f"(c[3])
                 : "r"(a[0]), "r"(a[1]), "r"(a[2]), "r"(a[3]), "r"(b0), "r"(b1));
}
__device__ __forceinline__ uint32_t movm(uint32_t a) {
    uint32_t d;
    asm volatile("movmatrix.sync.aligned.m8n8.trans.b16 %0, %1;" : "=r"(d) : "r"(a));
    return d;
}
__device__ __forceinline__ uint32_t pack_bf16(float lo, float hi) {
    uint32_t d;
    asm("cvt.rn.bf16x2.f32 %0, %1, %2;" : "=r"(d) : "f"(hi), "f"(lo));
    return d;
}
__device__ __forceinline__ float bf_lo(uint32_t u) { return __uint_as_float(u << 16); }
__device__ __forceinline__ float bf_hi(uint32_t u) { return __uint_as_float(u & 0xffff0000u); }
__device__ __forceinline__ float bfr(float v) { return __uint_as_float(pack_bf16(0.f, v)); }
__device__ __forceinline__ uint32_t max_bf16x2(uint32_t a, uint32_t b) {
    uint32_t d;
    asm("max.bf16x2 %0, %1, %2;" : "=r"(d) : "r"(a), "r"(b));
    return d;
}
__device__ __forceinline__ float ex2(float x) {
    float y;
    asm("ex2.approx.ftz.f32 %0, %1;" : "=f"(y) : "f"(x));
    return y;
}
__device__ __forceinline__ float mul_sigmoid(float v, float z) { return __fdividef(v, 1.0f + ex2(fminf(-kLog2e * z, 120.f))); }
__device__ __forceinline__ uint32_t lds32(uint32_t a) { uint32_t v; asm volatile("ld.shared.u32 %0, [%1];" : "=r"(v) : "r"(a) : "memory"); return v; }
__device__ __forceinline__ float2 ldsf2(uint32_t a) { float2 v; asm volatile("ld.shared.v2.f32 {%0,%1}, [%2];" : "=f"(v.x), "=f"(v.y) : "r"(a) : "memory"); return v; }
__device__ __forceinline__ uint4 lds128(uint32_t a) {
    uint4 v;
    asm volatile("ld.shared.v4.u32 {%0,%1,%2,%3}, [%4];" : "=r"(v.x), "=r"(v.y), "=r"(v.z), "=r"(v.w) : "r"(a) : "memory");
    return v;
}
__device__ __forceinline__ void sts32(uint32_t a, uint32_t v) { asm volatile("st.shared.u32 [%0], %1;" ::"r"(a), "r"(v) : "memory"); }
__device__ __forceinline__ void stsf(uint32_t a, float v) { asm volatile("st.shared.f32 [%0], %1;" ::"r"(a), "f"(v) : "memory"); }
__device__ __forceinline__ void sts128(uint32_t a, uint32_t x, uint32_t y, uint32_t z, uint32_t w) {
    asm volatile("st.shared.v4.u32 [%0], {%1,%2,%3,%4};" ::"r"(a), "r"(x), "r"(y), "r"(z), "r"(w) : "memory");
}
__device__ __forceinline__ uint32_t enc(uint32_t b) { return b == 0u ? 0x80000000u : b; }
__device__ __forceinline__ void st_pred32(void* p, uint32_t v, bool c) {
    asm volatile("{\n.reg .pred p;\nsetp.ne.u32 p, %2, 0;\n@p st.global.u32 [%0], %1;\n}" ::"l"(p), "r"(v), "r"((uint32_t)c) : "memory");
}
__device__ __forceinline__ void ld_rlx4_pred(uint32_t (&v)[4], const uint32_t* p, bool c) {
    asm volatile("{\n.reg .pred p;\nsetp.ne.u32 p, %5, 0;\n@p ld.relaxed.gpu.global.v4.u32 {%0,%1,%2,%3}, [%4];\n}"
                 : "+r"(v[0]), "+r"(v[1]), "+r"(v[2]), "+r"(v[3]) : "l"(p), "r"((uint32_t)c) : "memory");
}
__device__ __forceinline__ uint32_t gt32() { uint32_t c; asm volatile("mov.u32 %0, %globaltimer_lo;" : "=r"(c) :: "memory"); return c; }
__device__ __forceinline__ void wait_until(uint32_t t0, int ns) {
    while (gt32() - t0 < (uint32_t)max(ns, 0)) {}
}
__device__ __forceinline__ uint32_t ldg32(const void* p) {
    uint32_t v;
    asm volatile("ld.global.nc.u32 %0, [%1];" : "=r"(v) : "l"(p));
    return v;
}

__global__ void __cluster_dims__(8, 1, 1) __launch_bounds__(kThreads, 1)
fused_decode_kernel(const __nv_bfloat16* __restrict__ x, const __nv_bfloat16* __restrict__ b1,
                    const __nv_bfloat16* __restrict__ b2, __nv_bfloat16* __restrict__ out, const char* __restrict__ kc,
                    const __grid_constant__ Params prm) {
    extern __shared__ __align__(1024) unsigned char smem_raw[];
    const uint32_t sb = smem_u32(smem_raw);
    const uint32_t bars = sb + SM_BAR;
    const int tid = threadIdx.x, wid = tid >> 5, lane = tid & 31;
    const int hkv = blockIdx.x >> 3, r = blockIdx.x & 7;
    asm volatile("{\n.reg .pred p;\nsetp.lt.u32 p, %1, %2;\n@p prefetch.global.L2 [%0];\n}"
                 ::"l"(kc + ((r * kHKV + hkv) * (kSK * 256u) + tid * 128u)), "r"(tid), "n"(PFN) : "memory");
    if (tid < 32) {
        if (elect_one()) {
            mbar_init(bars + B_FULL, 1);
            mbar_init(bars + B_FULL + 8, 1);
            asm volatile("fence.mbarrier_init.release.cluster;" ::: "memory");
#pragma unroll
            for (int n = 0; n < 2; n++) {
                mbar_expect_tx(bars + B_FULL + 8 * n, kSlot);
                tma3d(sb + SM_RING + n * kSlot, &prm.m[2], blockIdx.x * 64, n * 256, 0, bars + B_FULL + 8 * n);
            }
#pragma unroll
            for (int n = 2; n < kNSlot; n++) mbar_init(bars + B_FULL + 8 * n, 1);
            asm volatile("fence.mbarrier_init.release.cluster;" ::: "memory");
            mbar_expect_tx(bars + B_FULL + 16, r < 7 ? kSlot : 0);
            if (r < 7) tma3d(sb + SM_RING + 2 * kSlot, &prm.m[3], hkv * 224 + r * 32, 0, 0, bars + B_FULL + 16);
        }
    }
    const uint32_t t_start = gt32();
    if (wid == 1) asm volatile("prefetch.global.L1 [%0];" ::"l"(x + r * kD + lane * 16) : "memory");
    if (wid == 3 && lane < 4) asm volatile("prefetch.tensormap [%0];" ::"l"(&prm.m[lane + (lane & 2)]) : "memory");
    if (tid == 64) {
        if (sb & 1023u) __trap();
#pragma unroll
        for (int n = 0; n < kNSlot; n++) mbar_init(bars + B_EMPTY + 8 * n, 8);
#pragma unroll
        for (int n = B_WO; n < B_END; n += 8) mbar_init(bars + n, n < B_H ? 1 : 8);
        asm volatile("fence.mbarrier_init.release.cluster;" ::: "memory");
        sts128(sb + SM_PROG, 0, 0, 0, 0);
        sts128(sb + SM_PROG + 16, 0, 0, 0, 0);
        asm volatile("fence.release.sync_restrict::shared::cta.cluster;" ::: "memory");
        mbar_expect_tx(bars + B_X, 8192);
        mbar_expect_tx(bars + B_Q, 1024);
        mbar_expect_tx(bars + B_Y, 2048);
        mbar_expect_tx(bars + B_S, 2048);
    }
    __syncwarp();
    cluster_arrive();
    const int w = (wid - 2) & 7;
    const int g = lane >> 2, t = lane & 3, r7 = lane & 7, mi = lane >> 3;

    if (wid == 1) {
        {
            const uint4* xr = reinterpret_cast<const uint4*>(x + r * kD) + lane;
            const uint4 xv0 = __ldg(xr), xv1 = __ldg(xr + 32);
            float f[16];
            const uint32_t u[8] = {xv0.x, xv0.y, xv0.z, xv0.w, xv1.x, xv1.y, xv1.z, xv1.w};
#pragma unroll
            for (int i = 0; i < 8; i++) { f[2 * i] = bf_lo(u[i]); f[2 * i + 1] = bf_hi(u[i]); }
            float s = 0.f;
#pragma unroll
            for (int i = 0; i < 16; i++) s += f[i];
#pragma unroll
            for (int o = 16; o; o >>= 1) s += __shfl_xor_sync(0xffffffffu, s, o);
            const float mean = s * (1.0f / kD);
            float vs = 0.f;
#pragma unroll
            for (int i = 0; i < 16; i++) { const float d = f[i] - mean; vs = fmaf(d, d, vs); }
#pragma unroll
            for (int o = 16; o; o >>= 1) vs += __shfl_xor_sync(0xffffffffu, vs, o);
            const float mb = bfr(mean);
            const float den = bfr(__fsqrt_rn(bfr(bfr(vs * (1.0f / kD)) + 1e-5f)));
            const float rden = __frcp_rn(den);
            uint32_t q[8];
#pragma unroll
            for (int i = 0; i < 8; i++) {
                const uint32_t d2 = pack_bf16(f[2 * i] - mb, f[2 * i + 1] - mb);
                q[i] = pack_bf16(bf_lo(d2) * rden, bf_hi(d2) * rden);
            }
            const uint32_t xoff = SM_X + r * 1024 + ((lane >> 1) & 7) * 128 + (((2 * (lane >> 4) + (lane & 1)) ^ r) << 4);
            cluster_wait();
#pragma unroll 1
            for (int d = 0; d < 8; d++) {
                const uint32_t rb = mapa(sb, d), xa = rb + xoff;
                st_async4(xa, q[0], q[1], q[2], q[3], rb + SM_BAR + B_X);
                st_async4(xa ^ 64, q[4], q[5], q[6], q[7], rb + SM_BAR + B_X);
            }
        }
        const int col = hkv * 64 + 2 * lane;
        const uint32_t xw = ldg32(x + r * kD + col), bw = ldg32(b2 + col);
        __nv_bfloat16* dst = out + r * kD + col;
        uint32_t pa = sb + SM_Y + lane * 8, pbar = bars + B_Y;
        PINL(dst);
        uint32_t gw = 0u;
#pragma unroll 1
        for (int pass = 0; pass < 2; pass++) {
            mbar_wait_cl(pbar, 0);
            float2 v[8];
#pragma unroll
            for (int c = 0; c < 8; c++) v[c] = ldsf2(pa + c * 256);
            const uint32_t sw = pack_bf16(((v[0].x + v[1].x) + (v[2].x + v[3].x)) + ((v[4].x + v[5].x) + (v[6].x + v[7].x)),
                                          ((v[0].y + v[1].y) + (v[2].y + v[3].y)) + ((v[4].y + v[5].y) + (v[6].y + v[7].y)));
            uint32_t ow;
            asm("{\n.reg .b32 p;\nmul.rn.bf16x2 p, %1, %2;\nadd.rn.bf16x2 %0, %3, p;\n}" : "=r"(ow) : "r"(sw), "r"(gw), "r"(xw));
            st_pred32(dst, ow, pass);
            if (pass) break;
            const uint32_t yw = pack_bf16(bf_lo(sw) + bf_lo(bw), bf_hi(sw) + bf_hi(bw));
            gw = pack_bf16(mul_sigmoid(bf_lo(yw), bf_lo(yw)), mul_sigmoid(bf_hi(yw), bf_hi(yw)));
            pa = sb + SM_S + lane * 8;
            pbar = bars + B_S;
        }
    } else if (wid == 0) {
        cluster_wait();
        const int kvrow0 = (r * kHKV + hkv) * kSK;
        const uint32_t prog_remote = mapa(sb + SM_PROG + r * 4, lane & 7);
        uint64_t stream_pol;
        asm volatile("createpolicy.fractional.L2::evict_first.b64 %0, 1.0;" : "=l"(stream_pol));
        int slot = kKVN, ph = 0;
        int landed = 0, lslot = 0, lph = 0;
#pragma unroll 1
        for (int n = kKVN; n < kItems; n++) {
            if (n >= kNSlot) mbar_wait(bars + B_EMPTY + 8 * slot, ph ^ 1);
            for (const int need = n - (n >= kW2N ? kWindowEnd : kWindow); landed <= need; landed++) {
                mbar_wait(bars + B_FULL + 8 * lslot, lph);
                if (++lslot == kNSlot) { lslot = 0; lph ^= 1; }
            }
            wait_until(t_start, n < kHeadN ? kHeadT0 + (n - kKVN) * kHeadDt
                                           : prm.sched_a + n * prm.sched_b + (n < kW2N ? 0 : n < kWoN ? kGapW2 : kGapWo));
            if (n < kW2N) {
                if (lane < 8) asm volatile("st.relaxed.cluster.shared::cluster.u32 [%0], %1;" ::"r"(prog_remote), "r"(n) : "memory");
                for (uint32_t it = 0;; it++) {
                    int p;
                    asm volatile("ld.relaxed.cluster.shared::cta.u32 %0, [%1];" : "=r"(p) : "r"(sb + SM_PROG + (lane & 7) * 4) : "memory");
                    if (__all_sync(0xffffffffu, max(p, kKVN) + kLead >= n)) break;
                    if (it > kSpinLimit * 16) __trap();
                }
            }
            if (elect_one()) {
                const uint32_t dst = sb + SM_RING + slot * kSlot;
                if (n < kW2N) {
                    const int u = n - kKVN;
                    mbar_expect_tx(bars + B_FULL + 8 * slot, kSlot);
                    tma3d_hint(dst, &prm.m[(u >> 4) & 1], 0, 0, kvrow0 + (u >> 5) * 2048 + (u & 15) * 128, bars + B_FULL + 8 * slot, stream_pol);
                } else if (n >= kWoN) {
                    const uint32_t wb = bars + B_WO + 16 * (n - kWoN);
                    mbar_expect_tx(wb, kSlot / 2);
                    tma4d(dst, &prm.m[5], hkv * 64, 0, 0, r * 32 + (n - kWoN) * 16, wb);
                    mbar_expect_tx(wb + 8, kSlot / 2);
                    tma4d(dst + kSlot / 2, &prm.m[5], hkv * 64, 0, 0, r * 32 + (n - kWoN) * 16 + 8, wb + 8);
                } else {
                    mbar_expect_tx(bars + B_W2, 224 * 128);
                    tma3d(dst, &prm.m[4], hkv * 64, r * 224, 0, bars + B_W2);
                }
                if (n == kGoN) mbar_arrive(bars + B_GO);
            }
            __syncwarp();
            if (++slot == kNSlot) { slot = 0; ph ^= 1; }
        }
        wait_until(gt32(), kGateO);
        mbar_wait(bars + B_W2, 0);
        if (lane == 0) mbar_arrive(bars + B_GO2);
    } else if (wid < 10) {
        const int kg = w >> 1, ch = w & 1;
        if (w == 7 && lane < 16) sts32(sb + SM_B1 + lane * 4, ldg32(b1 + hkv * 224 + (r < 7 ? r : 0) * 32 + 2 * lane));
        uint32_t wa = sb + SM_SCR + kg * 2176 + t * 544 + (ch * 32 + g) * 4;
        uint32_t ra = sb + SM_SCR + w * 272 + lane * 8;
        uint32_t* op = &g_o[hkv][r][kg * 512 + lane * 4];
        const uint32_t baddr = sb + SM_X + r7 * 1024 + (mi & 1) * 512 + (((2 * kg + (mi >> 1)) ^ r7) << 4);
        uint32_t abase = sb + SM_RING + kg * (kSlot / 2) + (r7 + 64 * (mi >> 1)) * 128 + (((4 * ch + (mi & 1)) ^ r7) << 4);
        uint32_t abar = bars + B_FULL + 8 * (kg >> 1);
        uint32_t sa = mapa(sb + SM_S + r * 256 + lane * 8, w), sbar = mapa(bars + B_S, w);
        PIN(wa); PIN(ra); PINL(op); PIN(sa); PIN(sbar);
        uint32_t bf[4][4];
        auto fetch_o = [&]() {
            bool all = true;
#pragma unroll
            for (int j = 0; j < 4; j++) {
                const bool ok = bf[j][0] != 0u && bf[j][1] != 0u && bf[j][2] != 0u && bf[j][3] != 0u;
                all = all && ok;
                ld_rlx4_pred(bf[j], op + j * 128, !ok);
            }
            return __all_sync(0xffffffffu, all);
        };
        cluster_wait();
        mbar_wait_cl(bars + B_X, 0);
#pragma unroll 1
        for (int pass = 0; pass < 3; pass++) {
            float acc[2][2][4];
#pragma unroll
            for (int i = 0; i < 16; i++) acc[i >> 3][(i >> 2) & 1][i & 3] = 0.f;
            bool stream = true;
            if (pass == 2) {
                mbar_wait(bars + B_GO2, 0);
                for (uint32_t it = 0;; it++) {
                    stream = fetch_o();
                    if (stream || kg < 2 || __all_sync(0xffffffffu, mbar_test(abar, 0))) break;
                    if (it > kSpinLimit) __trap();
                }
            } else {
#pragma unroll
                for (int i = 0; i < 4; i++) ldsm4(bf[i], baddr + ((i + 2 * (pass & ch)) & 3) * 128);
            }
            if (pass == 1) {
                const uint32_t a1 = sb + SM_RING + 2 * kSlot + (128 * kg + 32 * ch + r7 + 64 * (mi >> 1)) * 64 + (((mi & 1) ^ (r7 >> 1)) << 4);
                mbar_wait(bars + B_FULL + 16, 0);
#pragma unroll
                for (int ks = 0; ks < 4; ks++) {
#pragma unroll
                    for (int mt = 0; mt < 2; mt++) {
                        uint32_t af[4];
                        ldsm4t(af, (a1 ^ (mt * 32)) + (ks >> 1) * 1024 + (ks & 1) * 512);
                        mma16816(acc[mt][ks & 1], af, bf[ks >> 1][2 * (ks & 1)], bf[ks >> 1][2 * (ks & 1) + 1]);
                    }
                }
            } else if (stream) {
                mbar_wait(abar, 0);
#pragma unroll
                for (int ks = 0; ks < 8; ks++) {
#pragma unroll
                    for (int mt = 0; mt < 2; mt++) {
                        uint32_t af[4];
                        ldsm4t(af, (abase ^ (mt * 32)) + ks * 1024);
                        mma16816(acc[mt][ks & 1], af, bf[ks >> 1][2 * (ks & 1)], bf[ks >> 1][2 * (ks & 1) + 1]);
                    }
                }
            } else {
                uint32_t af[8][2][4];
                mbar_wait(abar, 0);
#pragma unroll
                for (int ks = 0; ks < 8; ks++) {
                    ldsm4t(af[ks][0], abase + ks * 1024);
                    ldsm4t(af[ks][1], (abase ^ 32) + ks * 1024);
                }
                for (uint32_t it = 0; !fetch_o(); it++)
                    if (it > kSpinLimit) __trap();
#pragma unroll
                for (int ks = 0; ks < 8; ks++) {
                    mma16816(acc[0][ks & 1], af[ks][0], bf[ks >> 1][2 * (ks & 1)], bf[ks >> 1][2 * (ks & 1) + 1]);
                    mma16816(acc[1][ks & 1], af[ks][1], bf[ks >> 1][2 * (ks & 1)], bf[ks >> 1][2 * (ks & 1) + 1]);
                }
            }
#pragma unroll
            for (int mt = 0; mt < 2; mt++) {
#pragma unroll
                for (int e = 0; e < 4; e++)
                    stsf(wa + (e & 1) * 272 + (mt * 16 + 8 * (e >> 1)) * 4, acc[mt][0][e] + acc[mt][1][e]);
            }
            bar_sync(1, 256);
            const float2 p0 = ldsf2(ra), p1 = ldsf2(ra + 2176), p2 = ldsf2(ra + 2 * 2176), p3 = ldsf2(ra + 3 * 2176);
            float s0 = (p0.x + p1.x) + (p2.x + p3.x), s1 = (p0.y + p1.y) + (p2.y + p3.y);
            st_async2_pred(sa, s0, s1, sbar, pass == 2);
            if (pass == 2) break;
            if (pass == 0) {
                const uint32_t rb = mapa(sb, w);
                st_async(rb + SM_Q + (r * 32 + lane) * 4, pack_bf16(s0, s1), rb + SM_BAR + B_Q);
                if (lane == 0) mbar_arrive_n(bars + B_EMPTY + 8 * (kg >> 1), 2);
            } else {
                if (lane == 0) mbar_arrive(bars + B_EMPTY + 16);
                s0 += __shfl_xor_sync(0xffffffffu, s0, 16);
                s1 += __shfl_xor_sync(0xffffffffu, s1, 16);
                const uint32_t sw = pack_bf16(s0, s1), b1w = lds32(sb + SM_B1 + (lane & 15) * 4);
                const uint32_t vw = pack_bf16(bf_lo(sw) + bf_lo(b1w), bf_hi(sw) + bf_hi(b1w));
                const float v0 = bf_lo(vw), v1 = bf_hi(vw);
                const float c = 2.0f * 0.7978845608028654f;
                uint32_t hw = pack_bf16(mul_sigmoid(v0, c * (v0 + 0.044715f * v0 * v0 * v0)),
                                        mul_sigmoid(v1, c * (v1 + 0.044715f * v1 * v1 * v1)));
                hw = r < 7 ? enc(hw) : 0x80000000u;
                {
                    uint32_t* cp = &g_o[w][hkv][(g * 16 + r) * 16 + t * 4];
                    *reinterpret_cast<uint4*>(cp) = make_uint4(0u, 0u, 0u, 0u);
                    *reinterpret_cast<uint4*>(cp + 128) = make_uint4(0u, 0u, 0u, 0u);
                    __threadfence();
                    bar_sync(1, 256);
                }
                {
                    uint32_t* hp = &g_h[(lane >> 4) * 4][hkv][w * 128 + (2 * (r & 1) + (mi & 1)) * 32 + (((2 * (r >> 1) + (r7 >> 2)) ^ w) << 2) + t];
#pragma unroll
                    for (int d = 0; d < 4; d++) asm volatile("st.relaxed.gpu.global.u32 [%0], %1;" ::"l"(hp + d * 8 * 1024), "r"(hw) : "memory");
                }
                mbar_wait(bars + B_GO, 0);
                {
                    uint32_t* hp = &g_h[hkv][r][w * 128 + lane * 4];
                    uint4 v;
                    for (uint32_t it = 0;; it++) {
                        asm volatile("ld.relaxed.gpu.global.v4.u32 {%0,%1,%2,%3}, [%4];" : "=r"(v.x), "=r"(v.y), "=r"(v.z), "=r"(v.w) : "l"(hp) : "memory");
                        if (v.x != 0u && v.y != 0u && v.z != 0u && v.w != 0u) break;
                        if (it > kSpinLimit) __trap();
                    }
                    sts128(sb + SM_H + w * 512 + lane * 16, v.x, v.y, v.z, v.w);
                    *reinterpret_cast<uint4*>(hp) = make_uint4(0u, 0u, 0u, 0u);
                    __threadfence();
                }
                __syncwarp();
                if (lane == 0) mbar_arrive(bars + B_H);
#pragma unroll
                for (int i = 0; i < 16; i++) bf[i >> 2][i & 3] = 0u;
                abase += (kWoN % kNSlot) * kSlot;
                abar = bars + B_WO + 8 * kg;
                PIN(abase); PIN(abar);
            }
            bar_sync(1, 256);
        }
    } else {
        int slot = kKVN, ph = 0;
        auto acquire = [&]() {
            mbar_wait(bars + B_FULL + 8 * slot, ph);
            return sb + SM_RING + slot * kSlot;
        };
        auto release = [&]() {
            __syncwarp();
            if (lane == 0) mbar_arrive_n(bars + B_EMPTY + 8 * slot, 2);
            if (++slot == kNSlot) { slot = 0; ph ^= 1; }
        };
        const int hl = r7 >> 2;
        const bool diag = (g >> 2) == (t >> 1);
        uint32_t koff[4];
#pragma unroll
        for (int c = 0; c < 4; c++)
            koff[c] = (w * 32 + r7 + 8 * (mi & 1)) * 256 + hl * 128 + (((2 * c + (mi >> 1)) ^ (2 * (r7 & 3) + hl)) << 4);
        const uint32_t voff = (16 * (mi >> 1) + r7 + 8 * hl) * 256 + hl * 128 + (((2 * w + (mi & 1)) ^ (2 * (r7 & 3) + hl)) << 4);
        const int ht = 2 * (t & 1) + (t >> 1);
        uint32_t* op = &g_o[0][hkv][((ht * 4 + w) * 8 + r) * 16 + (g & 3) * 4 + 2 * (g >> 2)];
        PINL(op);
        cluster_wait();
        uint32_t qf[8][2];
        mbar_wait_cl(bars + B_Q, 0);
#pragma unroll
        for (int ks = 0; ks < 8; ks++) {
            qf[ks][0] = lds32(sb + SM_Q + ((g & 3) * 64 + (ks ^ (g & 4)) * 8 + t) * 4);
            qf[ks][1] = lds32(sb + SM_Q + ((g & 3) * 64 + (ks ^ (g & 4)) * 8 + 4 + t) * 4);
        }
        uint32_t mx2 = 0xff7fff7fu;
        uint32_t mprev = 0xff7fff7fu;
        float Mw = bf_hi(mprev), l = 0.f, fin = 0.f;
        float O[4][4];
#pragma unroll
        for (int i = 0; i < 4; i++) { O[i][0] = O[i][1] = O[i][2] = O[i][3] = 0.f; }
#pragma unroll 1
        for (int c = 0; c < 2; c++) {
            uint32_t pa = sb + SM_P + (g & 3) * kPStride + (diag ? 0 : 16) + t * 4 + w * 64;
#pragma unroll 1
            for (int it = 0; it < 16; it++) {
                const uint32_t base = acquire();
                float sc[2][2][4];
#pragma unroll
                for (int i = 0; i < 16; i++) sc[i >> 3][(i >> 2) & 1][i & 3] = 0.f;
#pragma unroll
                for (int ks = 0; ks < 8; ks++) {
#pragma unroll
                    for (int mt = 0; mt < 2; mt++) {
                        uint32_t kf[4];
                        ldsm4(kf, base + (koff[ks & 3] ^ ((ks >> 2) * 144)) + mt * 4096);
                        mma16816(sc[mt][ks & 1], kf, qf[ks][0], qf[ks][1]);
                    }
                }
                release();
#pragma unroll
                for (int mt = 0; mt < 2; mt++) {
                    const uint32_t sa = pack_bf16(sc[mt][0][0] + sc[mt][1][0], sc[mt][0][1] + sc[mt][1][1]);
                    const uint32_t sx = __shfl_xor_sync(0xffffffffu, pack_bf16(sc[mt][0][2] + sc[mt][1][2], sc[mt][0][3] + sc[mt][1][3]), 2);
                    const uint32_t s2 = diag ? sa : sx;
                    const float scale = 0.08838834764831845f;
                    const uint32_t v = pack_bf16(bf_lo(s2) * scale, bf_hi(s2) * scale);
                    mx2 = max_bf16x2(mx2, v);
                    sts32(pa + mt * 32, movm(v));
                }
                pa += it == 7 ? 4 * kPStride - 7 * 256 : 256;
            }
            {
#pragma unroll
                for (int o = 2; o <= 16; o <<= 1) mx2 = max_bf16x2(mx2, __shfl_xor_sync(0xffffffffu, mx2, o));
                if (lane < 2) sts32(sb + SM_ML + lane * 16 + w * 4, mx2);
                bar_sync(2, 128);
                const uint4 a0 = lds128(sb + SM_ML), b0 = lds128(sb + SM_ML + 16);
                const uint32_t m01 = max_bf16x2(max_bf16x2(a0.x, a0.y), max_bf16x2(a0.z, a0.w));
                const uint32_t m23 = max_bf16x2(max_bf16x2(b0.x, b0.y), max_bf16x2(b0.z, b0.w));
                const uint32_t mw = (w & 2) ? m23 : m01, mt = (t & 1) ? m23 : m01;
                const float M = (w & 1) ? bf_hi(mw) : bf_lo(mw);
                l *= ex2((Mw - M) * kLog2e);
                Mw = M;
                const float al0 = ex2((bf_lo(mprev) - bf_lo(mt)) * kLog2e), al1 = ex2((bf_hi(mprev) - bf_hi(mt)) * kLog2e);
                mprev = mt;
#pragma unroll
                for (int i = 0; i < 4; i++) { O[i][0] *= al0; O[i][1] *= al1; O[i][2] *= al0; O[i][3] *= al1; }
                const uint32_t ea = sb + SM_P + w * kPStride + lane * 16;
#pragma unroll 2
                for (int i = 0; i < 8; i++) {
                    const uint32_t ei = ea + (i >> 2) * (4 * kPStride) + (i & 3) * 512;
                    const uint4 sv = lds128(ei);
                    const uint32_t uu[4] = {sv.x, sv.y, sv.z, sv.w};
                    uint32_t rr[4];
#pragma unroll
                    for (int e = 0; e < 4; e++) {
                        const float p0 = ex2((bf_lo(uu[e]) - M) * kLog2e), p1 = ex2((bf_hi(uu[e]) - M) * kLog2e);
                        l += p0 + p1;
                        rr[e] = pack_bf16(p0, p1);
                    }
                    sts128(ei, rr[0], rr[1], rr[2], rr[3]);
                }
                float ls = l;
#pragma unroll
                for (int o = 16; o; o >>= 1) ls += __shfl_xor_sync(0xffffffffu, ls, o);
                if (lane == 0) stsf(sb + SM_ML + 32 + w * 4, ls);
                bar_sync(2, 128);
                fin = __fdividef(1.0f, __uint_as_float(lds32(sb + SM_ML + 32 + ht * 4)));
                PINF(fin);
                if (c == 1) mbar_wait(bars + B_H, 0);
            }
            pa = sb + SM_P + (r7 & 3) * kPStride + (r7 >> 2) * 16 + mi * 32;
#pragma unroll 1
            for (int it = 0; it < 16; it++) {
                uint32_t pf[2][4], ps[2][8];
                ldsm4(pf[0], pa);
                ldsm4(pf[1], pa + 128);
                pa += it == 7 ? 4 * kPStride - 7 * 256 : 256;
#pragma unroll
                for (int i = 0; i < 8; i++) {
                    ps[0][i] = diag ? pf[i >> 2][i & 3] : 0u;
                    ps[1][i] = diag ? 0u : pf[i >> 2][i & 3];
                }
                const uint32_t base = acquire();
#pragma unroll
                for (int j = 0; j < 4; j++) {
#pragma unroll
                    for (int i = 0; i < 4; i++) {
                        uint32_t vf[4];
                        ldsm4t(vf, base + (voff ^ ((i >> 1) * 144 + (i & 1) * 2048)) + j * 8192);
                        mma16816(O[2 * ((i >> 1) ^ (i & 1)) + (i & 1)], vf, ps[i & 1][2 * j], ps[i & 1][2 * j + 1]);
                    }
                }
                release();
            }
        }
        uint32_t ow[2];
        float Z[2][4];
#pragma unroll
        for (int i = 0; i < 8; i++) Z[i >> 2][i & 3] = O[2 * (i >> 2)][i & 3] + O[2 * (i >> 2) + 1][i & 3];
#pragma unroll
        for (int mt = 0; mt < 2; mt++) {
            const float (&A)[4] = Z[mt];
            const float (&B)[4] = Z[mt ^ 1];
            const float lo = (t < 2 ? A[0] : B[1]) + __shfl_xor_sync(0xffffffffu, t < 2 ? A[1] : B[0], 2);
            const float hi = (t < 2 ? A[2] : B[3]) + __shfl_xor_sync(0xffffffffu, t < 2 ? A[3] : B[2], 2);
            ow[mt] = enc(pack_bf16(lo * fin, hi * fin));
        }
#pragma unroll
        for (int d = 0; d < 8; d++)
            asm volatile("st.relaxed.gpu.global.v2.u32 [%0], {%1,%2};" ::"l"(op + d * kHKV * 2048), "r"(ow[0]), "r"(ow[1]) : "memory");
        {
            uint32_t hf[7][4];
#pragma unroll
            for (int j = 0; j < 7; j++)
                ldsm4(hf[j], sb + SM_H + r7 * 512 + (2 * (j & 1) + (mi >> 1)) * 128 + (((2 * (j >> 1) + (mi & 1)) ^ r7) << 4));
            uint32_t wa2 = sb + SM_RING + (kW2N % kNSlot) * kSlot + (r7 + 8 * (mi >> 1)) * 128 + (((2 * w + (mi & 1)) ^ r7) << 4);
            uint32_t ya = mapa(sb + SM_Y + r * 256 + (16 * w + g) * 4, 2 * t), yb = mapa(bars + B_Y, 2 * t), wbar = bars + B_W2;
            const uint32_t ostep = mapa(bars + B_Y, 2 * t + 1) - yb;
            PIN(wa2); PIN(ya); PIN(yb); PIN(wbar);
            {
                mbar_wait(wbar, 0);
                float acc[4][4];
#pragma unroll
                for (int i = 0; i < 16; i++) acc[i >> 2][i & 3] = 0.f;
#pragma unroll
                for (int ks = 0; ks < 14; ks++) {
                    uint32_t af[4];
                    ldsm4t(af, wa2 + ks * 2048);
                    mma16816(acc[ks & 3], af, hf[ks >> 1][2 * (ks & 1)], hf[ks >> 1][2 * (ks & 1) + 1]);
                }
#pragma unroll
                for (int e = 0; e < 4; e++)
                    st_async(ya + (e & 1) * ostep + (e >> 1) * 32, __float_as_uint((acc[0][e] + acc[1][e]) + (acc[2][e] + acc[3][e])),
                             yb + (e & 1) * ostep);
            }
        }
    }
}

typedef CUresult (*EncodeFn)(CUtensorMap*, CUtensorMapDataType, cuuint32_t, void*, const cuuint64_t*, const cuuint64_t*,
                             const cuuint32_t*, const cuuint32_t*, CUtensorMapInterleave, CUtensorMapSwizzle,
                             CUtensorMapL2promotion, CUtensorMapFloatOOBfill);

void encode(EncodeFn fn, CUtensorMap* m, void* p, int rank, const cuuint64_t* dims, const cuuint64_t* strides,
            const cuuint32_t* box, CUtensorMapSwizzle sw = CU_TENSOR_MAP_SWIZZLE_128B) {
    const cuuint32_t es[4] = {1, 1, 1, 1};
    fn(m, CU_TENSOR_MAP_DATA_TYPE_BFLOAT16, rank, p, dims, strides, box, es, CU_TENSOR_MAP_INTERLEAVE_NONE,
       sw, CU_TENSOR_MAP_L2_PROMOTION_NONE, CU_TENSOR_MAP_FLOAT_OOB_FILL_NONE);
}

}

extern "C" void kernel_launch(void* const* d_in, const int* in_sizes, int n_in, void* d_out, int out_size) {
    (void)in_sizes; (void)n_in; (void)out_size;
    void* fnp = nullptr;
    cudaDriverEntryPointQueryResult qr;
    cudaGetDriverEntryPoint("cuTensorMapEncodeTiled", &fnp, cudaEnableDefault, &qr);
    EncodeFn fn = (EncodeFn)fnp;
    Params prm;
    {
        const cuuint64_t dims[3] = {64, 2, (cuuint64_t)8 * kHKV * kSK}, str[2] = {128, 256};
        const cuuint32_t box[3] = {64, 2, 128};
        encode(fn, &prm.m[0], d_in[1], 3, dims, str, box);
        encode(fn, &prm.m[1], d_in[2], 3, dims, str, box);
    }
    {
        const cuuint64_t dims[3] = {4096, 512, 1}, str[2] = {8192, 8192 * 512};
        const cuuint32_t box[3] = {64, 256, 1};
        encode(fn, &prm.m[2], d_in[3], 3, dims, str, box);
    }
    {
        const cuuint64_t dims[3] = {1792, 256, 2}, str[2] = {3584, 3584 * 256};
        const cuuint32_t box[3] = {32, 256, 2};
        encode(fn, &prm.m[3], d_in[6], 3, dims, str, box, CU_TENSOR_MAP_SWIZZLE_64B);
    }
    {
        const cuuint64_t dims[3] = {512, 1792, 1}, str[2] = {1024, 1024 * 1792};
        const cuuint32_t box[3] = {64, 224, 1};
        encode(fn, &prm.m[4], d_in[8], 3, dims, str, box);
    }
    {
        const cuuint64_t dims[4] = {512, 2, 8, 256}, str[3] = {8 * 1024, 1024, 16 * 1024};
        const cuuint32_t box[4] = {64, 2, 8, 8};
        encode(fn, &prm.m[5], d_in[4], 4, dims, str, box);
    }
    {
        int dev = 0, khz = 0, bits = 0;
        cudaGetDevice(&dev);
        cudaDeviceGetAttribute(&khz, cudaDevAttrMemoryClockRate, dev);
        cudaDeviceGetAttribute(&bits, cudaDevAttrGlobalMemoryBusWidth, dev);
        const double bytes_per_ns = 2.0 * khz * 1e-6 * bits / 8.0;
        const double scale = bytes_per_ns > 1000.0 ? (double)kGrid * kSlot / bytes_per_ns / kItemNs : 0.0;
        prm.sched_b = (int)(SCHED_B * scale + 0.5);
        prm.sched_a = (int)(SCHED_E * scale + 0.5) - (kItems - 1) * prm.sched_b;
    }
    cudaFuncSetAttribute(fused_decode_kernel, cudaFuncAttributeMaxDynamicSharedMemorySize, SM_BYTES);
    fused_decode_kernel<<<kGrid, kThreads, SM_BYTES>>>(
        (const __nv_bfloat16*)d_in[0], (const __nv_bfloat16*)d_in[7], (const __nv_bfloat16*)d_in[9],
        (__nv_bfloat16*)d_out, (const char*)d_in[1], prm);
}
```

```cpp
#include <cuda_runtime.h>
#include <cuda_bf16.h>
#include <cuda.h>
#include <stdint.h>

namespace {

constexpr int kD = 512, kHKV = 8, kSK = 4096;
constexpr int kGrid = 64;
constexpr int kWarps = 14, kThreads = kWarps * 32;
constexpr int kSlot = 32768;
constexpr int kNSlot = 6;
constexpr int kItems = 70;
constexpr int kKVN = 3, kW2N = 67, kWoN = 68;
constexpr int kWindow = 4, kWindowEnd = 3;
constexpr int kLead = 1;
constexpr int kGoN = 40;
#define SCHED_E 43160
constexpr double kItemNs = 625.6, kSchedStep = 646, kSchedLast = SCHED_E;
constexpr int kHeadN = 6, kHeadT0 = 900, kHeadDt = 550;
constexpr int kGapW2 = 360, kGapWo = 275, kGateO = 325;
static_assert(kWindow >= 3 && kWindow < kNSlot && kNSlot <= 8 && kGoN < kKVN + 40, "ring");
static_assert(kWoN % kNSlot + 1 < kNSlot, "wo occupies two consecutive slots");

constexpr int kPStride = 2048 + 32;
constexpr int SM_RING = 0;
constexpr int SM_H = kNSlot * kSlot;
constexpr int SM_P = SM_H + 8 * 512;
constexpr int SM_X = SM_P + 4 * kPStride;
constexpr int SM_SCR = SM_X + 4 * kPStride;
constexpr int SM_Q = SM_SCR + 4 * 2176;
constexpr int SM_Y = SM_Q + 1024;
constexpr int SM_S = SM_Y + 2048;
constexpr int SM_ML = SM_S + 2048;
constexpr int SM_B1 = SM_ML + 64;
constexpr int SM_PROG = SM_B1 + 64;
constexpr int SM_BAR = SM_PROG + 32;
constexpr int B_FULL = 0, B_EMPTY = 8 * kNSlot, B_WO = 16 * kNSlot, B_W2 = B_WO + 32, B_GO = B_W2 + 8, B_GO2 = B_GO + 8,
              B_X = B_GO2 + 8, B_Q = B_X + 8, B_Y = B_Q + 8, B_S = B_Y + 8, B_H = B_S + 8, B_END = B_H + 8;
constexpr int SM_BYTES = SM_BAR + B_END;
static_assert(SM_BYTES <= 232448, "smem");

constexpr float kLog2e = 1.4426950408889634f;
constexpr uint32_t kSpinLimit = 1u << 22;
constexpr long long kWaitCycles = 1ll << 32;

struct Params {
    CUtensorMap m[6];
    int sched_a, sched_b;
};

__device__ __align__(128) uint32_t g_o[8][kHKV][2048];
__device__ __align__(128) uint32_t g_h[8][8][1024];

__device__ __forceinline__ uint32_t smem_u32(const void* p) { return (uint32_t)__cvta_generic_to_shared(p); }
__device__ __forceinline__ void mbar_init(uint32_t bar, uint32_t cnt) {
    asm volatile("mbarrier.init.shared::cta.b64 [%0], %1;" ::"r"(bar), "r"(cnt) : "memory");
}
__device__ __forceinline__ void mbar_expect_tx(uint32_t bar, uint32_t bytes) {
    asm volatile("mbarrier.arrive.expect_tx.shared::cta.b64 _, [%0], %1;" ::"r"(bar), "r"(bytes) : "memory");
}
__device__ __forceinline__ void mbar_arrive(uint32_t bar) {
    asm volatile("mbarrier.arrive.shared::cta.b64 _, [%0];" ::"r"(bar) : "memory");
}
__device__ __forceinline__ void mbar_arrive_n(uint32_t bar, uint32_t n) {
    asm volatile("mbarrier.arrive.shared::cta.b64 _, [%0], %1;" ::"r"(bar), "r"(n) : "memory");
}
__device__ __forceinline__ bool mbar_try(uint32_t bar, uint32_t parity) {
    uint32_t ok;
    asm volatile("{\n.reg .pred p;\nmbarrier.try_wait.parity.relaxed.cluster.shared::cta.b64 p, [%1], %2;\nselp.u32 %0, 1, 0, p;\n}"
                 : "=r"(ok) : "r"(bar), "r"(parity) : "memory");
    return ok != 0u;
}
__device__ __forceinline__ bool mbar_try_cta(uint32_t bar, uint32_t parity) {
    uint32_t ok;
    asm volatile("{\n.reg .pred p;\nmbarrier.try_wait.parity.shared::cta.b64 p, [%1], %2;\nselp.u32 %0, 1, 0, p;\n}"
                 : "=r"(ok) : "r"(bar), "r"(parity) : "memory");
    return ok != 0u;
}
__device__ __forceinline__ bool mbar_test(uint32_t bar, uint32_t parity) {
    uint32_t ok;
    asm volatile("{\n.reg .pred p;\nmbarrier.test_wait.parity.shared::cta.b64 p, [%1], %2;\nselp.u32 %0, 1, 0, p;\n}"
                 : "=r"(ok) : "r"(bar), "r"(parity) : "memory");
    return ok != 0u;
}
__device__ __forceinline__ void mbar_wait(uint32_t bar, uint32_t parity) {
    if (mbar_try_cta(bar, parity)) return;
    const long long t0 = clock64();
    while (!mbar_try_cta(bar, parity))
        if (clock64() - t0 > kWaitCycles) __trap();
}
__device__ __forceinline__ void mbar_wait_cl(uint32_t bar, uint32_t parity) {
    if (!mbar_try(bar, parity)) {
        const long long t0 = clock64();
        while (!mbar_try(bar, parity))
            if (clock64() - t0 > kWaitCycles) __trap();
    }
    asm volatile("fence.acquire.sync_restrict::shared::cluster.cluster;" ::: "memory");
}
#define PIN(x) asm volatile("shfl.sync.bfly.b32 %0, %0, 0, 0x1f, 0xffffffff;" : "+r"(x) :: "memory")
#define PINF(x) asm volatile("" : "+f"(x) :: "memory")
#define PINL(x) asm volatile("{\n.reg .b32 lo, hi;\nmov.b64 {lo, hi}, %0;\nshfl.sync.bfly.b32 lo, lo, 0, 0x1f, 0xffffffff;\n" \
                             "shfl.sync.bfly.b32 hi, hi, 0, 0x1f, 0xffffffff;\nmov.b64 %0, {lo, hi};\n}" : "+l"(x) :: "memory")
__device__ __forceinline__ void tma4d(uint32_t dst, const CUtensorMap* m, int c0, int c1, int c2, int c3, uint32_t bar) {
    asm volatile("cp.async.bulk.tensor.4d.shared::cluster.global.mbarrier::complete_tx::bytes [%0], [%1, {%3, %4, %5, %6}], [%2];"
                 ::"r"(dst), "l"(m), "r"(bar), "r"(c0), "r"(c1), "r"(c2), "r"(c3) : "memory");
}
__device__ __forceinline__ void tma3d(uint32_t dst, const CUtensorMap* m, int c0, int c1, int c2, uint32_t bar) {
    asm volatile("cp.async.bulk.tensor.3d.shared::cluster.global.mbarrier::complete_tx::bytes [%0], [%1, {%3, %4, %5}], [%2];"
                 ::"r"(dst), "l"(m), "r"(bar), "r"(c0), "r"(c1), "r"(c2) : "memory");
}
__device__ __forceinline__ void tma3d_hint(uint32_t dst, const CUtensorMap* m, int c0, int c1, int c2, uint32_t bar, uint64_t pol) {
    asm volatile("cp.async.bulk.tensor.3d.shared::cluster.global.mbarrier::complete_tx::bytes.L2::cache_hint [%0], [%1, {%3, %4, %5}], [%2], %6;"
                 ::"r"(dst), "l"(m), "r"(bar), "r"(c0), "r"(c1), "r"(c2), "l"(pol) : "memory");
}
__device__ __forceinline__ void bar_sync(int id, int n) { asm volatile("barrier.sync %0, %1;" ::"r"(id), "r"(n) : "memory"); }
__device__ __forceinline__ bool elect_one() {
    uint32_t p;
    asm volatile("{\n.reg .pred p;\nelect.sync _|p, 0xffffffff;\nselp.u32 %0, 1, 0, p;\n}" : "=r"(p));
    return p != 0u;
}
__device__ __forceinline__ void cluster_arrive() { asm volatile("barrier.cluster.arrive.relaxed;" ::: "memory"); }
__device__ __forceinline__ void cluster_wait() { asm volatile("barrier.cluster.wait;" ::: "memory"); }
__device__ __forceinline__ uint32_t mapa(uint32_t a, uint32_t rank) {
    uint32_t d;
    asm("mapa.shared::cluster.u32 %0, %1, %2;" : "=r"(d) : "r"(a), "r"(rank));
    return d;
}
__device__ __forceinline__ void st_async(uint32_t a, uint32_t v, uint32_t bar) {
    asm volatile("st.async.shared::cluster.mbarrier::complete_tx::bytes.u32 [%0], %1, [%2];" ::"r"(a), "r"(v), "r"(bar) : "memory");
}
__device__ __forceinline__ void st_async2_pred(uint32_t a, float x, float y, uint32_t bar, bool c) {
    asm volatile("{\n.reg .pred p;\nsetp.ne.u32 p, %4, 0;\n@p st.async.shared::cluster.mbarrier::complete_tx::bytes.v2.f32 [%0], {%1,%2}, [%3];\n}"
                 ::"r"(a), "f"(x), "f"(y), "r"(bar), "r"((uint32_t)c) : "memory");
}
__device__ __forceinline__ void st_async4(uint32_t a, uint32_t x, uint32_t y, uint32_t z, uint32_t w, uint32_t bar) {
    asm volatile("st.async.shared::cluster.mbarrier::complete_tx::bytes.v4.u32 [%0], {%1,%2,%3,%4}, [%5];"
                 ::"r"(a), "r"(x), "r"(y), "r"(z), "r"(w), "r"(bar) : "memory");
}

__device__ __forceinline__ void ldsm4(uint32_t (&r)[4], uint32_t a) {
    asm volatile("ldmatrix.sync.aligned.m8n8.x4.shared.b16 {%0,%1,%2,%3}, [%4];"
                 : "=r"(r[0]), "=r"(r[1]), "=r"(r[2]), "=r"(r[3]) : "r"(a) : "memory");
}
__device__ __forceinline__ void ldsm4t(uint32_t (&r)[4], uint32_t a) {
    asm volatile("ldmatrix.sync.aligned.m8n8.x4.trans.shared.b16 {%0,%1,%2,%3}, [%4];"
                 : "=r"(r[0]), "=r"(r[1]), "=r"(r[2]), "=r"(r[3]) : "r"(a) : "memory");
}
__device__ __forceinline__ void mma16816(float (&c)[4], const uint32_t (&a)[4], uint32_t b0, uint32_t b1) {
    asm volatile("mma.sync.aligned.m16n8k16.row.col.f32.bf16.bf16.f32 {%0,%1,%2,%3}, {%4,%5,%6,%7}, {%8,%9}, {%0,%1,%2,%3};"
                 : "+f"(c[0]), "+f"(c[1]), "+f"(c[2]), "+f"(c[3])
                 : "r"(a[0]), "r"(a[1]), "r"(a[2]), "r"(a[3]), "r"(b0), "r"(b1));
}
__device__ __forceinline__ uint32_t movm(uint32_t a) {
    uint32_t d;
    asm volatile("movmatrix.sync.aligned.m8n8.trans.b16 %0, %1;" : "=r"(d) : "r"(a));
    return d;
}
__device__ __forceinline__ uint32_t pack_bf16(float lo, float hi) {
    uint32_t d;
    asm("cvt.rn.bf16x2.f32 %0, %1, %2;" : "=r"(d) : "f"(hi), "f"(lo));
    return d;
}
__device__ __forceinline__ float bf_lo(uint32_t u) { return __uint_as_float(u << 16); }
__device__ __forceinline__ float bf_hi(uint32_t u) { return __uint_as_float(u & 0xffff0000u); }
__device__ __forceinline__ float bfr(float v) { return __uint_as_float(pack_bf16(0.f, v)); }
__device__ __forceinline__ uint32_t max_bf16x2(uint32_t a, uint32_t b) {
    uint32_t d;
    asm("max.bf16x2 %0, %1, %2;" : "=r"(d) : "r"(a), "r"(b));
    return d;
}
__device__ __forceinline__ float ex2(float x) {
    float y;
    asm("ex2.approx.ftz.f32 %0, %1;" : "=f"(y) : "f"(x));
    return y;
}
__device__ __forceinline__ float mul_sigmoid(float v, float z) { return __fdividef(v, 1.0f + ex2(fminf(-kLog2e * z, 120.f))); }
__device__ __forceinline__ uint32_t lds32(uint32_t a) { uint32_t v; asm volatile("ld.shared.u32 %0, [%1];" : "=r"(v) : "r"(a) : "memory"); return v; }
__device__ __forceinline__ float2 ldsf2(uint32_t a) { float2 v; asm volatile("ld.shared.v2.f32 {%0,%1}, [%2];" : "=f"(v.x), "=f"(v.y) : "r"(a) : "memory"); return v; }
__device__ __forceinline__ uint4 lds128(uint32_t a) {
    uint4 v;
    asm volatile("ld.shared.v4.u32 {%0,%1,%2,%3}, [%4];" : "=r"(v.x), "=r"(v.y), "=r"(v.z), "=r"(v.w) : "r"(a) : "memory");
    return v;
}
__device__ __forceinline__ void sts32(uint32_t a, uint32_t v) { asm volatile("st.shared.u32 [%0], %1;" ::"r"(a), "r"(v) : "memory"); }
__device__ __forceinline__ void stsf(uint32_t a, float v) { asm volatile("st.shared.f32 [%0], %1;" ::"r"(a), "f"(v) : "memory"); }
__device__ __forceinline__ void sts128(uint32_t a, uint32_t x, uint32_t y, uint32_t z, uint32_t w) {
    asm volatile("st.shared.v4.u32 [%0], {%1,%2,%3,%4};" ::"r"(a), "r"(x), "r"(y), "r"(z), "r"(w) : "memory");
}
__device__ __forceinline__ uint32_t enc(uint32_t b) { return b == 0u ? 0x80000000u : b; }
__device__ __forceinline__ void st_pred32(void* p, uint32_t v, bool c) {
    asm volatile("{\n.reg .pred p;\nsetp.ne.u32 p, %2, 0;\n@p st.global.u32 [%0], %1;\n}" ::"l"(p), "r"(v), "r"((uint32_t)c) : "memory");
}
__device__ __forceinline__ void ld_rlx4_pred(uint32_t (&v)[4], const uint32_t* p, bool c) {
    asm volatile("{\n.reg .pred p;\nsetp.ne.u32 p, %5, 0;\n@p ld.relaxed.gpu.global.v4.u32 {%0,%1,%2,%3}, [%4];\n}"
                 : "+r"(v[0]), "+r"(v[1]), "+r"(v[2]), "+r"(v[3]) : "l"(p), "r"((uint32_t)c) : "memory");
}
__device__ __forceinline__ uint32_t gt32() { uint32_t c; asm volatile("mov.u32 %0, %globaltimer_lo;" : "=r"(c) :: "memory"); return c; }
__device__ __forceinline__ void wait_until(uint32_t t0, int ns) {
    while (gt32() - t0 < (uint32_t)max(ns, 0)) {}
}
__device__ __forceinline__ uint32_t ldg32(const void* p) {
    uint32_t v;
    asm volatile("ld.global.nc.u32 %0, [%1];" : "=r"(v) : "l"(p));
    return v;
}

__global__ void __cluster_dims__(8, 1, 1) __launch_bounds__(kThreads, 1)
fused_decode_kernel(const __nv_bfloat16* __restrict__ x, const __nv_bfloat16* __restrict__ b1,
                    const __nv_bfloat16* __restrict__ b2, __nv_bfloat16* __restrict__ out, const char* __restrict__ kc,
                    const __grid_constant__ Params prm) {
    extern __shared__ __align__(1024) unsigned char smem_raw[];
    const uint32_t sb = smem_u32(smem_raw);
    const uint32_t bars = sb + SM_BAR;
    const int tid = threadIdx.x, wid = tid >> 5, lane = tid & 31;
    const int hkv = blockIdx.x >> 3, r = blockIdx.x & 7;
    const int flip = (hkv & 1) * 2;
    asm volatile("{\n.reg .pred p;\nsetp.lt.u32 p, %1, %2;\n@p prefetch.global.L2 [%0];\n}"
                 ::"l"(kc + ((r * kHKV + hkv) * (kSK * 256u) + flip * (uint32_t)kSlot + tid * 128u)), "r"(tid), "n"(96) : "memory");
    if (tid < 32) {
        if (elect_one()) {
            mbar_init(bars + B_FULL, 1);
            mbar_init(bars + B_FULL + 8, 1);
            asm volatile("fence.mbarrier_init.release.cluster;" ::: "memory");
#pragma unroll
            for (int n = 0; n < 2; n++) {
                mbar_expect_tx(bars + B_FULL + 8 * n, kSlot);
                tma3d(sb + SM_RING + n * kSlot, &prm.m[2], blockIdx.x * 64, n * 256, 0, bars + B_FULL + 8 * n);
            }
#pragma unroll
            for (int n = 2; n < kNSlot; n++) mbar_init(bars + B_FULL + 8 * n, 1);
            asm volatile("fence.mbarrier_init.release.cluster;" ::: "memory");
            mbar_expect_tx(bars + B_FULL + 16, r < 7 ? kSlot : 0);
            if (r < 7) tma3d(sb + SM_RING + 2 * kSlot, &prm.m[3], hkv * 224 + r * 32, 0, 0, bars + B_FULL + 16);
        }
    }
    const uint32_t t_start = gt32();
    if (wid == 1) asm volatile("prefetch.global.L1 [%0];" ::"l"(x + r * kD + lane * 16) : "memory");
    if (wid == 3 && lane < 4) asm volatile("prefetch.tensormap [%0];" ::"l"(&prm.m[lane + (lane & 2)]) : "memory");
    if (tid == 64) {
        if (sb & 1023u) __trap();
#pragma unroll
        for (int n = 0; n < kNSlot; n++) mbar_init(bars + B_EMPTY + 8 * n, 8);
#pragma unroll
        for (int n = B_WO; n < B_END; n += 8) mbar_init(bars + n, n < B_H ? 1 : 8);
        asm volatile("fence.mbarrier_init.release.cluster;" ::: "memory");
        sts128(sb + SM_PROG, 0, 0, 0, 0);
        sts128(sb + SM_PROG + 16, 0, 0, 0, 0);
        asm volatile("fence.release.sync_restrict::shared::cta.cluster;" ::: "memory");
        mbar_expect_tx(bars + B_X, 8192);
        mbar_expect_tx(bars + B_Q, 1024);
        mbar_expect_tx(bars + B_Y, 2048);
        mbar_expect_tx(bars + B_S, 2048);
    }
    __syncwarp();
    cluster_arrive();
    const int w = (wid - 2) & 7;
    const int g = lane >> 2, t = lane & 3, r7 = lane & 7, mi = lane >> 3;

    if (wid == 1) {
        {
            const uint4* xr = reinterpret_cast<const uint4*>(x + r * kD) + lane;
            const uint4 xv0 = __ldg(xr), xv1 = __ldg(xr + 32);
            float f[16];
            const uint32_t u[8] = {xv0.x, xv0.y, xv0.z, xv0.w, xv1.x, xv1.y, xv1.z, xv1.w};
#pragma unroll
            for (int i = 0; i < 8; i++) { f[2 * i] = bf_lo(u[i]); f[2 * i + 1] = bf_hi(u[i]); }
            float s = 0.f;
#pragma unroll
            for (int i = 0; i < 16; i++) s += f[i];
#pragma unroll
            for (int o = 16; o; o >>= 1) s += __shfl_xor_sync(0xffffffffu, s, o);
            const float mean = s * (1.0f / kD);
            float vs = 0.f;
#pragma unroll
            for (int i = 0; i < 16; i++) { const float d = f[i] - mean; vs = fmaf(d, d, vs); }
#pragma unroll
            for (int o = 16; o; o >>= 1) vs += __shfl_xor_sync(0xffffffffu, vs, o);
            const float mb = bfr(mean);
            const float den = bfr(__fsqrt_rn(bfr(bfr(vs * (1.0f / kD)) + 1e-5f)));
            const float rden = __frcp_rn(den);
            uint32_t q[8];
#pragma unroll
            for (int i = 0; i < 8; i++) {
                const uint32_t d2 = pack_bf16(f[2 * i] - mb, f[2 * i + 1] - mb);
                q[i] = pack_bf16(bf_lo(d2) * rden, bf_hi(d2) * rden);
            }
            const uint32_t xoff = SM_X + r * 1024 + ((lane >> 1) & 7) * 128 + (((2 * (lane >> 4) + (lane & 1)) ^ r) << 4);
            cluster_wait();
#pragma unroll 1
            for (int d = 0; d < 8; d++) {
                const uint32_t rb = mapa(sb, d), xa = rb + xoff;
                st_async4(xa, q[0], q[1], q[2], q[3], rb + SM_BAR + B_X);
                st_async4(xa ^ 64, q[4], q[5], q[6], q[7], rb + SM_BAR + B_X);
            }
        }
        const int col = hkv * 64 + 2 * lane;
        const uint32_t xw = ldg32(x + r * kD + col), bw = ldg32(b2 + col);
        __nv_bfloat16* dst = out + r * kD + col;
        uint32_t pa = sb + SM_Y + lane * 8, pbar = bars + B_Y;
        PINL(dst);
        uint32_t gw = 0u;
#pragma unroll 1
        for (int pass = 0; pass < 2; pass++) {
            mbar_wait_cl(pbar, 0);
            float2 v[8];
#pragma unroll
            for (int c = 0; c < 8; c++) v[c] = ldsf2(pa + c * 256);
            const uint32_t sw = pack_bf16(((v[0].x + v[1].x) + (v[2].x + v[3].x)) + ((v[4].x + v[5].x) + (v[6].x + v[7].x)),
                                          ((v[0].y + v[1].y) + (v[2].y + v[3].y)) + ((v[4].y + v[5].y) + (v[6].y + v[7].y)));
            uint32_t ow;
            asm("{\n.reg .b32 p;\nmul.rn.bf16x2 p, %1, %2;\nadd.rn.bf16x2 %0, %3, p;\n}" : "=r"(ow) : "r"(sw), "r"(gw), "r"(xw));
            st_pred32(dst, ow, pass);
            if (pass) break;
            const uint32_t yw = pack_bf16(bf_lo(sw) + bf_lo(bw), bf_hi(sw) + bf_hi(bw));
            gw = pack_bf16(mul_sigmoid(bf_lo(yw), bf_lo(yw)), mul_sigmoid(bf_hi(yw), bf_hi(yw)));
            pa = sb + SM_S + lane * 8;
            pbar = bars + B_S;
        }
    } else if (wid == 0) {
        cluster_wait();
        const int kvrow0 = (r * kHKV + hkv) * kSK;
        const uint32_t prog_remote = mapa(sb + SM_PROG + r * 4, lane & 7);
        uint64_t stream_pol;
        asm volatile("createpolicy.fractional.L2::evict_first.b64 %0, 1.0;" : "=l"(stream_pol));
        int slot = kKVN, ph = 0;
        int landed = 0, lslot = 0, lph = 0;
#pragma unroll 1
        for (int n = kKVN; n < kItems; n++) {
            if (n >= kNSlot) mbar_wait(bars + B_EMPTY + 8 * slot, ph ^ 1);
            for (const int need = n - (n >= kW2N ? kWindowEnd : kWindow); landed <= need; landed++) {
                mbar_wait(bars + B_FULL + 8 * lslot, lph);
                if (++lslot == kNSlot) { lslot = 0; lph ^= 1; }
            }
            wait_until(t_start, n < kHeadN ? kHeadT0 + (n - kKVN) * kHeadDt
                                           : prm.sched_a + n * prm.sched_b + (n < kW2N ? 0 : n < kWoN ? kGapW2 : kGapWo));
            if (n < kW2N) {
                if (lane < 8) asm volatile("st.relaxed.cluster.shared::cluster.u32 [%0], %1;" ::"r"(prog_remote), "r"(n) : "memory");
                for (uint32_t it = 0;; it++) {
                    int p;
                    asm volatile("ld.relaxed.cluster.shared::cta.u32 %0, [%1];" : "=r"(p) : "r"(sb + SM_PROG + (lane & 7) * 4) : "memory");
                    if (__all_sync(0xffffffffu, max(p, kKVN) + kLead >= n)) break;
                    if (it > kSpinLimit * 16) __trap();
                }
            }
            if (elect_one()) {
                const uint32_t dst = sb + SM_RING + slot * kSlot;
                if (n < kW2N) {
                    const int u = n - kKVN;
                    mbar_expect_tx(bars + B_FULL + 8 * slot, kSlot);
                    tma3d_hint(dst, &prm.m[(u >> 4) & 1], 0, 0, kvrow0 + (u >> 5) * 2048 + ((u & 15) ^ flip) * 128, bars + B_FULL + 8 * slot, stream_pol);
                } else if (n >= kWoN) {
                    const uint32_t wb = bars + B_WO + 16 * (n - kWoN);
                    mbar_expect_tx(wb, kSlot / 2);
                    tma4d(dst, &prm.m[5], hkv * 64, 0, 0, r * 32 + (n - kWoN) * 16, wb);
                    mbar_expect_tx(wb + 8, kSlot / 2);
                    tma4d(dst + kSlot / 2, &prm.m[5], hkv * 64, 0, 0, r * 32 + (n - kWoN) * 16 + 8, wb + 8);
                } else {
                    mbar_expect_tx(bars + B_W2, 224 * 128);
                    tma3d(dst, &prm.m[4], hkv * 64, r * 224, 0, bars + B_W2);
                }
                if (n == kGoN) mbar_arrive(bars + B_GO);
            }
            __syncwarp();
            if (++slot == kNSlot) { slot = 0; ph ^= 1; }
        }
        wait_until(gt32(), kGateO);
        mbar_wait(bars + B_W2, 0);
        if (lane == 0) mbar_arrive(bars + B_GO2);
    } else if (wid < 10) {
        const int kg = w >> 1, ch = w & 1;
        if (w == 7 && lane < 16) sts32(sb + SM_B1 + lane * 4, ldg32(b1 + hkv * 224 + (r < 7 ? r : 0) * 32 + 2 * lane));
        uint32_t wa = sb + SM_SCR + kg * 2176 + t * 544 + (ch * 32 + g) * 4;
        uint32_t ra = sb + SM_SCR + w * 272 + lane * 8;
        uint32_t* op = &g_o[hkv][r][kg * 512 + lane * 4];
        const uint32_t baddr = sb + SM_X + r7 * 1024 + (mi & 1) * 512 + (((2 * kg + (mi >> 1)) ^ r7) << 4);
        uint32_t abase = sb + SM_RING + kg * (kSlot / 2) + (r7 + 64 * (mi >> 1)) * 128 + (((4 * ch + (mi & 1)) ^ r7) << 4);
        uint32_t abar = bars + B_FULL + 8 * (kg >> 1);
        uint32_t sa = mapa(sb + SM_S + r * 256 + lane * 8, w), sbar = mapa(bars + B_S, w);
        PIN(wa); PIN(ra); PINL(op); PIN(sa); PIN(sbar);
        uint32_t bf[4][4];
        auto fetch_o = [&]() {
            bool all = true;
#pragma unroll
            for (int j = 0; j < 4; j++) {
                const bool ok = bf[j][0] != 0u && bf[j][1] != 0u && bf[j][2] != 0u && bf[j][3] != 0u;
                all = all && ok;
                ld_rlx4_pred(bf[j], op + j * 128, !ok);
            }
            return __all_sync(0xffffffffu, all);
        };
        cluster_wait();
        mbar_wait_cl(bars + B_X, 0);
#pragma unroll 1
        for (int pass = 0; pass < 3; pass++) {
            float acc[2][2][4];
#pragma unroll
            for (int i = 0; i < 16; i++) acc[i >> 3][(i >> 2) & 1][i & 3] = 0.f;
            bool stream = true;
            if (pass == 2) {
                mbar_wait(bars + B_GO2, 0);
                for (uint32_t it = 0;; it++) {
                    stream = fetch_o();
                    if (stream || kg < 2 || __all_sync(0xffffffffu, mbar_test(abar, 0))) break;
                    if (it > kSpinLimit) __trap();
                }
            } else {
#pragma unroll
                for (int i = 0; i < 4; i++) ldsm4(bf[i], baddr + ((i + 2 * (pass & ch)) & 3) * 128);
            }
            if (pass == 1) {
                const uint32_t a1 = sb + SM_RING + 2 * kSlot + (128 * kg + 32 * ch + r7 + 64 * (mi >> 1)) * 64 + (((mi & 1) ^ (r7 >> 1)) << 4);
                mbar_wait(bars + B_FULL + 16, 0);
#pragma unroll
                for (int ks = 0; ks < 4; ks++) {
#pragma unroll
                    for (int mt = 0; mt < 2; mt++) {
                        uint32_t af[4];
                        ldsm4t(af, (a1 ^ (mt * 32)) + (ks >> 1) * 1024 + (ks & 1) * 512);
                        mma16816(acc[mt][ks & 1], af, bf[ks >> 1][2 * (ks & 1)], bf[ks >> 1][2 * (ks & 1) + 1]);
                    }
                }
            } else if (stream) {
                mbar_wait(abar, 0);
#pragma unroll
                for (int ks = 0; ks < 8; ks++) {
#pragma unroll
                    for (int mt = 0; mt < 2; mt++) {
                        uint32_t af[4];
                        ldsm4t(af, (abase ^ (mt * 32)) + ks * 1024);
                        mma16816(acc[mt][ks & 1], af, bf[ks >> 1][2 * (ks & 1)], bf[ks >> 1][2 * (ks & 1) + 1]);
                    }
                }
            } else {
                uint32_t af[8][2][4];
                mbar_wait(abar, 0);
#pragma unroll
                for (int ks = 0; ks < 8; ks++) {
                    ldsm4t(af[ks][0], abase + ks * 1024);
                    ldsm4t(af[ks][1], (abase ^ 32) + ks * 1024);
                }
                for (uint32_t it = 0; !fetch_o(); it++)
                    if (it > kSpinLimit) __trap();
#pragma unroll
                for (int ks = 0; ks < 8; ks++) {
                    mma16816(acc[0][ks & 1], af[ks][0], bf[ks >> 1][2 * (ks & 1)], bf[ks >> 1][2 * (ks & 1) + 1]);
                    mma16816(acc[1][ks & 1], af[ks][1], bf[ks >> 1][2 * (ks & 1)], bf[ks >> 1][2 * (ks & 1) + 1]);
                }
            }
#pragma unroll
            for (int mt = 0; mt < 2; mt++) {
#pragma unroll
                for (int e = 0; e < 4; e++)
                    stsf(wa + (e & 1) * 272 + (mt * 16 + 8 * (e >> 1)) * 4, acc[mt][0][e] + acc[mt][1][e]);
            }
            bar_sync(1, 256);
            const float2 p0 = ldsf2(ra), p1 = ldsf2(ra + 2176), p2 = ldsf2(ra + 2 * 2176), p3 = ldsf2(ra + 3 * 2176);
            float s0 = (p0.x + p1.x) + (p2.x + p3.x), s1 = (p0.y + p1.y) + (p2.y + p3.y);
            st_async2_pred(sa, s0, s1, sbar, pass == 2);
            if (pass == 2) break;
            if (pass == 0) {
                const uint32_t rb = mapa(sb, w);
                st_async(rb + SM_Q + (r * 32 + lane) * 4, pack_bf16(s0, s1), rb + SM_BAR + B_Q);
                if (lane == 0) mbar_arrive_n(bars + B_EMPTY + 8 * (kg >> 1), 2);
            } else {
                if (lane == 0) mbar_arrive(bars + B_EMPTY + 16);
                s0 += __shfl_xor_sync(0xffffffffu, s0, 16);
                s1 += __shfl_xor_sync(0xffffffffu, s1, 16);
                const uint32_t sw = pack_bf16(s0, s1), b1w = lds32(sb + SM_B1 + (lane & 15) * 4);
                const uint32_t vw = pack_bf16(bf_lo(sw) + bf_lo(b1w), bf_hi(sw) + bf_hi(b1w));
                const float v0 = bf_lo(vw), v1 = bf_hi(vw);
                const float c = 2.0f * 0.7978845608028654f;
                uint32_t hw = pack_bf16(mul_sigmoid(v0, c * (v0 + 0.044715f * v0 * v0 * v0)),
                                        mul_sigmoid(v1, c * (v1 + 0.044715f * v1 * v1 * v1)));
                hw = r < 7 ? enc(hw) : 0x80000000u;
                {
                    uint32_t* cp = &g_o[w][hkv][(g * 16 + r) * 16 + t * 4];
                    *reinterpret_cast<uint4*>(cp) = make_uint4(0u, 0u, 0u, 0u);
                    *reinterpret_cast<uint4*>(cp + 128) = make_uint4(0u, 0u, 0u, 0u);
                    __threadfence();
                    bar_sync(1, 256);
                }
                {
                    uint32_t* hp = &g_h[(lane >> 4) * 4][hkv][w * 128 + (2 * (r & 1) + (mi & 1)) * 32 + (((2 * (r >> 1) + (r7 >> 2)) ^ w) << 2) + t];
#pragma unroll
                    for (int d = 0; d < 4; d++) asm volatile("st.relaxed.gpu.global.u32 [%0], %1;" ::"l"(hp + d * 8 * 1024), "r"(hw) : "memory");
                }
                mbar_wait(bars + B_GO, 0);
                {
                    uint32_t* hp = &g_h[hkv][r][w * 128 + lane * 4];
                    uint4 v;
                    for (uint32_t it = 0;; it++) {
                        asm volatile("ld.relaxed.gpu.global.v4.u32 {%0,%1,%2,%3}, [%4];" : "=r"(v.x), "=r"(v.y), "=r"(v.z), "=r"(v.w) : "l"(hp) : "memory");
                        if (v.x != 0u && v.y != 0u && v.z != 0u && v.w != 0u) break;
                        if (it > kSpinLimit) __trap();
                    }
                    sts128(sb + SM_H + w * 512 + lane * 16, v.x, v.y, v.z, v.w);
                    *reinterpret_cast<uint4*>(hp) = make_uint4(0u, 0u, 0u, 0u);
                    __threadfence();
                }
                __syncwarp();
                if (lane == 0) mbar_arrive(bars + B_H);
#pragma unroll
                for (int i = 0; i < 16; i++) bf[i >> 2][i & 3] = 0u;
                abase += (kWoN % kNSlot) * kSlot;
                abar = bars + B_WO + 8 * kg;
                PIN(abase); PIN(abar);
            }
            bar_sync(1, 256);
        }
    } else {
        int slot = kKVN, ph = 0;
        auto acquire = [&]() {
            mbar_wait(bars + B_FULL + 8 * slot, ph);
            return sb + SM_RING + slot * kSlot;
        };
        auto release = [&]() {
            __syncwarp();
            if (lane == 0) mbar_arrive_n(bars + B_EMPTY + 8 * slot, 2);
            if (++slot == kNSlot) { slot = 0; ph ^= 1; }
        };
        const int hl = r7 >> 2;
        const bool diag = (g >> 2) == (t >> 1);
        uint32_t koff[4];
#pragma unroll
        for (int c = 0; c < 4; c++)
            koff[c] = (w * 32 + r7 + 8 * (mi & 1)) * 256 + hl * 128 + (((2 * c + (mi >> 1)) ^ (2 * (r7 & 3) + hl)) << 4);
        const uint32_t voff = (16 * (mi >> 1) + r7 + 8 * hl) * 256 + hl * 128 + (((2 * w + (mi & 1)) ^ (2 * (r7 & 3) + hl)) << 4);
        const int ht = 2 * (t & 1) + (t >> 1);
        uint32_t* op = &g_o[0][hkv][((ht * 4 + w) * 8 + r) * 16 + (g & 3) * 4 + 2 * (g >> 2)];
        PINL(op);
        cluster_wait();
        uint32_t qf[8][2];
        mbar_wait_cl(bars + B_Q, 0);
#pragma unroll
        for (int ks = 0; ks < 8; ks++) {
            qf[ks][0] = lds32(sb + SM_Q + ((g & 3) * 64 + (ks ^ (g & 4)) * 8 + t) * 4);
            qf[ks][1] = lds32(sb + SM_Q + ((g & 3) * 64 + (ks ^ (g & 4)) * 8 + 4 + t) * 4);
        }
        uint32_t mx2 = 0xff7fff7fu;
        uint32_t mprev = 0xff7fff7fu;
        float Mw = bf_hi(mprev), l = 0.f, fin = 0.f;
        float O[4][4];
#pragma unroll
        for (int i = 0; i < 4; i++) { O[i][0] = O[i][1] = O[i][2] = O[i][3] = 0.f; }
#pragma unroll 1
        for (int c = 0; c < 2; c++) {
            uint32_t pa = sb + SM_P + (g & 3) * kPStride + (diag ? 0 : 16) + t * 4 + w * 64;
#pragma unroll 1
            for (int it = 0; it < 16; it++) {
                const uint32_t base = acquire();
                float sc[2][2][4];
#pragma unroll
                for (int i = 0; i < 16; i++) sc[i >> 3][(i >> 2) & 1][i & 3] = 0.f;
#pragma unroll
                for (int ks = 0; ks < 8; ks++) {
#pragma unroll
                    for (int mt = 0; mt < 2; mt++) {
                        uint32_t kf[4];
                        ldsm4(kf, base + (koff[ks & 3] ^ ((ks >> 2) * 144)) + mt * 4096);
                        mma16816(sc[mt][ks & 1], kf, qf[ks][0], qf[ks][1]);
                    }
                }
                release();
#pragma unroll
                for (int mt = 0; mt < 2; mt++) {
                    const uint32_t sa = pack_bf16(sc[mt][0][0] + sc[mt][1][0], sc[mt][0][1] + sc[mt][1][1]);
                    const uint32_t sx = __shfl_xor_sync(0xffffffffu, pack_bf16(sc[mt][0][2] + sc[mt][1][2], sc[mt][0][3] + sc[mt][1][3]), 2);
                    const uint32_t s2 = diag ? sa : sx;
                    const float scale = 0.08838834764831845f;
                    const uint32_t v = pack_bf16(bf_lo(s2) * scale, bf_hi(s2) * scale);
                    mx2 = max_bf16x2(mx2, v);
                    sts32(pa + mt * 32, movm(v));
                }
                pa += it == 7 ? 4 * kPStride - 7 * 256 : 256;
            }
            {
#pragma unroll
                for (int o = 2; o <= 16; o <<= 1) mx2 = max_bf16x2(mx2, __shfl_xor_sync(0xffffffffu, mx2, o));
                if (lane < 2) sts32(sb + SM_ML + lane * 16 + w * 4, mx2);
                bar_sync(2, 128);
                const uint4 a0 = lds128(sb + SM_ML), b0 = lds128(sb + SM_ML + 16);
                const uint32_t m01 = max_bf16x2(max_bf16x2(a0.x, a0.y), max_bf16x2(a0.z, a0.w));
                const uint32_t m23 = max_bf16x2(max_bf16x2(b0.x, b0.y), max_bf16x2(b0.z, b0.w));
                const uint32_t mw = (w & 2) ? m23 : m01, mt = (t & 1) ? m23 : m01;
                const float M = (w & 1) ? bf_hi(mw) : bf_lo(mw);
                l *= ex2((Mw - M) * kLog2e);
                Mw = M;
                const float al0 = ex2((bf_lo(mprev) - bf_lo(mt)) * kLog2e), al1 = ex2((bf_hi(mprev) - bf_hi(mt)) * kLog2e);
                mprev = mt;
#pragma unroll
                for (int i = 0; i < 4; i++) { O[i][0] *= al0; O[i][1] *= al1; O[i][2] *= al0; O[i][3] *= al1; }
                const uint32_t ea = sb + SM_P + w * kPStride + lane * 16;
#pragma unroll 2
                for (int i = 0; i < 8; i++) {
                    const uint32_t ei = ea + (i >> 2) * (4 * kPStride) + (i & 3) * 512;
                    const uint4 sv = lds128(ei);
                    const uint32_t uu[4] = {sv.x, sv.y, sv.z, sv.w};
                    uint32_t rr[4];
#pragma unroll
                    for (int e = 0; e < 4; e++) {
                        const float p0 = ex2((bf_lo(uu[e]) - M) * kLog2e), p1 = ex2((bf_hi(uu[e]) - M) * kLog2e);
                        l += p0 + p1;
                        rr[e] = pack_bf16(p0, p1);
                    }
                    sts128(ei, rr[0], rr[1], rr[2], rr[3]);
                }
                float ls = l;
#pragma unroll
                for (int o = 16; o; o >>= 1) ls += __shfl_xor_sync(0xffffffffu, ls, o);
                if (lane == 0) stsf(sb + SM_ML + 32 + w * 4, ls);
                bar_sync(2, 128);
                fin = __fdividef(1.0f, __uint_as_float(lds32(sb + SM_ML + 32 + ht * 4)));
                PINF(fin);
                if (c == 1) mbar_wait(bars + B_H, 0);
            }
            pa = sb + SM_P + (r7 & 3) * kPStride + (r7 >> 2) * 16 + mi * 32;
#pragma unroll 1
            for (int it = 0; it < 16; it++) {
                uint32_t pf[2][4], ps[2][8];
                ldsm4(pf[0], pa);
                ldsm4(pf[1], pa + 128);
                pa += it == 7 ? 4 * kPStride - 7 * 256 : 256;
#pragma unroll
                for (int i = 0; i < 8; i++) {
                    ps[0][i] = diag ? pf[i >> 2][i & 3] : 0u;
                    ps[1][i] = diag ? 0u : pf[i >> 2][i & 3];
                }
                const uint32_t base = acquire();
#pragma unroll
                for (int j = 0; j < 4; j++) {
#pragma unroll
                    for (int i = 0; i < 4; i++) {
                        uint32_t vf[4];
                        ldsm4t(vf, base + (voff ^ ((i >> 1) * 144 + (i & 1) * 2048)) + j * 8192);
                        mma16816(O[2 * ((i >> 1) ^ (i & 1)) + (i & 1)], vf, ps[i & 1][2 * j], ps[i & 1][2 * j + 1]);
                    }
                }
                release();
            }
        }
        uint32_t ow[2];
        float Z[2][4];
#pragma unroll
        for (int i = 0; i < 8; i++) Z[i >> 2][i & 3] = O[2 * (i >> 2)][i & 3] + O[2 * (i >> 2) + 1][i & 3];
#pragma unroll
        for (int mt = 0; mt < 2; mt++) {
            const float (&A)[4] = Z[mt];
            const float (&B)[4] = Z[mt ^ 1];
            const float lo = (t < 2 ? A[0] : B[1]) + __shfl_xor_sync(0xffffffffu, t < 2 ? A[1] : B[0], 2);
            const float hi = (t < 2 ? A[2] : B[3]) + __shfl_xor_sync(0xffffffffu, t < 2 ? A[3] : B[2], 2);
            ow[mt] = enc(pack_bf16(lo * fin, hi * fin));
        }
#pragma unroll
        for (int d = 0; d < 8; d++)
            asm volatile("st.relaxed.gpu.global.v2.u32 [%0], {%1,%2};" ::"l"(op + d * kHKV * 2048), "r"(ow[0]), "r"(ow[1]) : "memory");
        {
            uint32_t hf[7][4];
#pragma unroll
            for (int j = 0; j < 7; j++)
                ldsm4(hf[j], sb + SM_H + r7 * 512 + (2 * (j & 1) + (mi >> 1)) * 128 + (((2 * (j >> 1) + (mi & 1)) ^ r7) << 4));
            uint32_t wa2 = sb + SM_RING + (kW2N % kNSlot) * kSlot + (r7 + 8 * (mi >> 1)) * 128 + (((2 * w + (mi & 1)) ^ r7) << 4);
            uint32_t ya = mapa(sb + SM_Y + r * 256 + (16 * w + g) * 4, 2 * t), yb = mapa(bars + B_Y, 2 * t), wbar = bars + B_W2;
            const uint32_t ostep = mapa(bars + B_Y, 2 * t + 1) - yb;
            PIN(wa2); PIN(ya); PIN(yb); PIN(wbar);
            {
                mbar_wait(wbar, 0);
                float acc[4][4];
#pragma unroll
                for (int i = 0; i < 16; i++) acc[i >> 2][i & 3] = 0.f;
#pragma unroll
                for (int ks = 0; ks < 14; ks++) {
                    uint32_t af[4];
                    ldsm4t(af, wa2 + ks * 2048);
                    mma16816(acc[ks & 3], af, hf[ks >> 1][2 * (ks & 1)], hf[ks >> 1][2 * (ks & 1) + 1]);
                }
#pragma unroll
                for (int e = 0; e < 4; e++)
                    st_async(ya + (e & 1) * ostep + (e >> 1) * 32, __float_as_uint((acc[0][e] + acc[1][e]) + (acc[2][e] + acc[3][e])),
                             yb + (e & 1) * ostep);
            }
        }
    }
}

typedef CUresult (*EncodeFn)(CUtensorMap*, CUtensorMapDataType, cuuint32_t, void*, const cuuint64_t*, const cuuint64_t*,
                             const cuuint32_t*, const cuuint32_t*, CUtensorMapInterleave, CUtensorMapSwizzle,
                             CUtensorMapL2promotion, CUtensorMapFloatOOBfill);

void encode(EncodeFn fn, CUtensorMap* m, void* p, int rank, const cuuint64_t* dims, const cuuint64_t* strides,
            const cuuint32_t* box, CUtensorMapSwizzle sw = CU_TENSOR_MAP_SWIZZLE_128B) {
    const cuuint32_t es[4] = {1, 1, 1, 1};
    fn(m, CU_TENSOR_MAP_DATA_TYPE_BFLOAT16, rank, p, dims, strides, box, es, CU_TENSOR_MAP_INTERLEAVE_NONE,
       sw, CU_TENSOR_MAP_L2_PROMOTION_NONE, CU_TENSOR_MAP_FLOAT_OOB_FILL_NONE);
}

}

extern "C" void kernel_launch(void* const* d_in, const int* in_sizes, int n_in, void* d_out, int out_size) {
    (void)in_sizes; (void)n_in; (void)out_size;
    void* fnp = nullptr;
    cudaDriverEntryPointQueryResult qr;
    cudaGetDriverEntryPoint("cuTensorMapEncodeTiled", &fnp, cudaEnableDefault, &qr);
    EncodeFn fn = (EncodeFn)fnp;
    Params prm;
    {
        const cuuint64_t dims[3] = {64, 2, (cuuint64_t)8 * kHKV * kSK}, str[2] = {128, 256};
        const cuuint32_t box[3] = {64, 2, 128};
        encode(fn, &prm.m[0], d_in[1], 3, dims, str, box);
        encode(fn, &prm.m[1], d_in[2], 3, dims, str, box);
    }
    {
        const cuuint64_t dims[3] = {4096, 512, 1}, str[2] = {8192, 8192 * 512};
        const cuuint32_t box[3] = {64, 256, 1};
        encode(fn, &prm.m[2], d_in[3], 3, dims, str, box);
    }
    {
        const cuuint64_t dims[3] = {1792, 256, 2}, str[2] = {3584, 3584 * 256};
        const cuuint32_t box[3] = {32, 256, 2};
        encode(fn, &prm.m[3], d_in[6], 3, dims, str, box, CU_TENSOR_MAP_SWIZZLE_64B);
    }
    {
        const cuuint64_t dims[3] = {512, 1792, 1}, str[2] = {1024, 1024 * 1792};
        const cuuint32_t box[3] = {64, 224, 1};
        encode(fn, &prm.m[4], d_in[8], 3, dims, str, box);
    }
    {
        const cuuint64_t dims[4] = {512, 2, 8, 256}, str[3] = {8 * 1024, 1024, 16 * 1024};
        const cuuint32_t box[4] = {64, 2, 8, 8};
        encode(fn, &prm.m[5], d_in[4], 4, dims, str, box);
    }
    {
        int dev = 0, khz = 0, bits = 0;
        cudaGetDevice(&dev);
        cudaDeviceGetAttribute(&khz, cudaDevAttrMemoryClockRate, dev);
        cudaDeviceGetAttribute(&bits, cudaDevAttrGlobalMemoryBusWidth, dev);
        const double bytes_per_ns = 2.0 * khz * 1e-6 * bits / 8.0;
        const double scale = bytes_per_ns > 1000.0 ? (double)kGrid * kSlot / bytes_per_ns / kItemNs : 0.0;
        prm.sched_b = (int)(kSchedStep * scale + 0.5);
        prm.sched_a = (int)(kSchedLast * scale + 0.5) - (kItems - 1) * prm.sched_b;
    }
    cudaFuncSetAttribute(fused_decode_kernel, cudaFuncAttributeMaxDynamicSharedMemorySize, SM_BYTES);
    fused_decode_kernel<<<kGrid, kThreads, SM_BYTES>>>(
        (const __nv_bfloat16*)d_in[0], (const __nv_bfloat16*)d_in[7], (const __nv_bfloat16*)d_in[9],
        (__nv_bfloat16*)d_out, (const char*)d_in[1], prm);
}
```

```cpp
#include <cuda_runtime.h>
#include <cuda_bf16.h>
#include <cuda.h>
#include <stdint.h>

namespace {

constexpr int kD = 512, kHKV = 8, kSK = 4096;
constexpr int kGrid = 64;
constexpr int kWarps = 14, kThreads = kWarps * 32;
constexpr int kSlot = 32768;
constexpr int kNSlot = 6;
constexpr int kItems = 70;
constexpr int kKVN = 3, kW2N = 67, kWoN = 68;
constexpr int kWindow = 4, kWindowEnd = 3;
constexpr int kLead = 1;
constexpr int kGoN = 40;
constexpr double kItemNs = 625.6, kSchedStep = 646, kSchedLast = 43180;
constexpr int kHeadN = 6, kHeadT0 = 900, kHeadDt = 550;
constexpr int kGapW2 = 360, kGapWo = 275, kGateO = 325;
static_assert(kWindow >= 3 && kWindow < kNSlot && kNSlot <= 8 && kGoN < kKVN + 40, "ring");
static_assert(kWoN % kNSlot + 1 < kNSlot, "wo occupies two consecutive slots");

constexpr int kPStride = 2048 + 32;
constexpr int SM_RING = 0;
constexpr int SM_H = kNSlot * kSlot;
constexpr int SM_P = SM_H + 8 * 512;
constexpr int SM_X = SM_P + 4 * kPStride;
constexpr int SM_SCR = SM_X + 4 * kPStride;
constexpr int SM_Q = SM_SCR + 4 * 2176;
constexpr int SM_Y = SM_Q + 1024;
constexpr int SM_S = SM_Y + 2048;
constexpr int SM_ML = SM_S + 2048;
constexpr int SM_B1 = SM_ML + 64;
constexpr int SM_PROG = SM_B1 + 64;
constexpr int SM_BAR = SM_PROG + 32;
constexpr int B_FULL = 0, B_EMPTY = 8 * kNSlot, B_WO = 16 * kNSlot, B_W2 = B_WO + 32, B_GO = B_W2 + 8, B_GO2 = B_GO + 8,
              B_X = B_GO2 + 8, B_Q = B_X + 8, B_Y = B_Q + 8, B_S = B_Y + 8, B_H = B_S + 8, B_END = B_H + 8;
constexpr int SM_BYTES = SM_BAR + B_END;
static_assert(SM_BYTES <= 232448, "smem");

constexpr float kLog2e = 1.4426950408889634f;
constexpr uint32_t kSpinLimit = 1u << 22;
constexpr long long kWaitCycles = 1ll << 32;

struct Params {
    CUtensorMap m[6];
    int sched_a, sched_b;
};

__device__ __align__(128) uint32_t g_o[8][kHKV][2048];
__device__ __align__(128) uint32_t g_h[8][8][1024];

__device__ __forceinline__ uint32_t smem_u32(const void* p) { return (uint32_t)__cvta_generic_to_shared(p); }
__device__ __forceinline__ void mbar_init(uint32_t bar, uint32_t cnt) {
    asm volatile("mbarrier.init.shared::cta.b64 [%0], %1;" ::"r"(bar), "r"(cnt) : "memory");
}
__device__ __forceinline__ void mbar_expect_tx(uint32_t bar, uint32_t bytes) {
    asm volatile("mbarrier.arrive.expect_tx.shared::cta.b64 _, [%0], %1;" ::"r"(bar), "r"(bytes) : "memory");
}
__device__ __forceinline__ void mbar_arrive(uint32_t bar) {
    asm volatile("mbarrier.arrive.shared::cta.b64 _, [%0];" ::"r"(bar) : "memory");
}
__device__ __forceinline__ void mbar_arrive_n(uint32_t bar, uint32_t n) {
    asm volatile("mbarrier.arrive.shared::cta.b64 _, [%0], %1;" ::"r"(bar), "r"(n) : "memory");
}
__device__ __forceinline__ bool mbar_try(uint32_t bar, uint32_t parity) {
    uint32_t ok;
    asm volatile("{\n.reg .pred p;\nmbarrier.try_wait.parity.relaxed.cluster.shared::cta.b64 p, [%1], %2;\nselp.u32 %0, 1, 0, p;\n}"
                 : "=r"(ok) : "r"(bar), "r"(parity) : "memory");
    return ok != 0u;
}
__device__ __forceinline__ bool mbar_try_cta(uint32_t bar, uint32_t parity) {
    uint32_t ok;
    asm volatile("{\n.reg .pred p;\nmbarrier.try_wait.parity.shared::cta.b64 p, [%1], %2;\nselp.u32 %0, 1, 0, p;\n}"
                 : "=r"(ok) : "r"(bar), "r"(parity) : "memory");
    return ok != 0u;
}
__device__ __forceinline__ bool mbar_test(uint32_t bar, uint32_t parity) {
    uint32_t ok;
    asm volatile("{\n.reg .pred p;\nmbarrier.test_wait.parity.shared::cta.b64 p, [%1], %2;\nselp.u32 %0, 1, 0, p;\n}"
                 : "=r"(ok) : "r"(bar), "r"(parity) : "memory");
    return ok != 0u;
}
__device__ __forceinline__ void mbar_wait(uint32_t bar, uint32_t parity) {
    if (mbar_try_cta(bar, parity)) return;
    const long long t0 = clock64();
    while (!mbar_try_cta(bar, parity))
        if (clock64() - t0 > kWaitCycles) __trap();
}
__device__ __forceinline__ void mbar_wait_cl(uint32_t bar, uint32_t parity) {
    if (!mbar_try(bar, parity)) {
        const long long t0 = clock64();
        while (!mbar_try(bar, parity))
            if (clock64() - t0 > kWaitCycles) __trap();
    }
    asm volatile("fence.acquire.sync_restrict::shared::cluster.cluster;" ::: "memory");
}
#define PIN(x) asm volatile("shfl.sync.bfly.b32 %0, %0, 0, 0x1f, 0xffffffff;" : "+r"(x) :: "memory")
#define PINF(x) asm volatile("" : "+f"(x) :: "memory")
#define PINL(x) asm volatile("{\n.reg .b32 lo, hi;\nmov.b64 {lo, hi}, %0;\nshfl.sync.bfly.b32 lo, lo, 0, 0x1f, 0xffffffff;\n" \
                             "shfl.sync.bfly.b32 hi, hi, 0, 0x1f, 0xffffffff;\nmov.b64 %0, {lo, hi};\n}" : "+l"(x) :: "memory")
__device__ __forceinline__ void tma4d(uint32_t dst, const CUtensorMap* m, int c0, int c1, int c2, int c3, uint32_t bar) {
    asm volatile("{\n.reg .b64 pol;\ncreatepolicy.fractional.L2::evict_first.b64 pol, 1.0;\n"
                 "cp.async.bulk.tensor.4d.shared::cluster.global.mbarrier::complete_tx::bytes.L2::cache_hint [%0], [%1, {%3, %4, %5, %6}], [%2], pol;\n}"
                 ::"r"(dst), "l"(m), "r"(bar), "r"(c0), "r"(c1), "r"(c2), "r"(c3) : "memory");
}
__device__ __forceinline__ void tma3d(uint32_t dst, const CUtensorMap* m, int c0, int c1, int c2, uint32_t bar) {
    asm volatile("{\n.reg .b64 pol;\ncreatepolicy.fractional.L2::evict_first.b64 pol, 1.0;\n"
                 "cp.async.bulk.tensor.3d.shared::cluster.global.mbarrier::complete_tx::bytes.L2::cache_hint [%0], [%1, {%3, %4, %5}], [%2], pol;\n}"
                 ::"r"(dst), "l"(m), "r"(bar), "r"(c0), "r"(c1), "r"(c2) : "memory");
}
__device__ __forceinline__ void bar_sync(int id, int n) { asm volatile("barrier.sync %0, %1;" ::"r"(id), "r"(n) : "memory"); }
__device__ __forceinline__ bool elect_one() {
    uint32_t p;
    asm volatile("{\n.reg .pred p;\nelect.sync _|p, 0xffffffff;\nselp.u32 %0, 1, 0, p;\n}" : "=r"(p));
    return p != 0u;
}
__device__ __forceinline__ void cluster_arrive() { asm volatile("barrier.cluster.arrive.relaxed;" ::: "memory"); }
__device__ __forceinline__ void cluster_wait() { asm volatile("barrier.cluster.wait;" ::: "memory"); }
__device__ __forceinline__ uint32_t mapa(uint32_t a, uint32_t rank) {
    uint32_t d;
    asm("mapa.shared::cluster.u32 %0, %1, %2;" : "=r"(d) : "r"(a), "r"(rank));
    return d;
}
__device__ __forceinline__ void st_async(uint32_t a, uint32_t v, uint32_t bar) {
    asm volatile("st.async.shared::cluster.mbarrier::complete_tx::bytes.u32 [%0], %1, [%2];" ::"r"(a), "r"(v), "r"(bar) : "memory");
}
__device__ __forceinline__ void st_async2_pred(uint32_t a, float x, float y, uint32_t bar, bool c) {
    asm volatile("{\n.reg .pred p;\nsetp.ne.u32 p, %4, 0;\n@p st.async.shared::cluster.mbarrier::complete_tx::bytes.v2.f32 [%0], {%1,%2}, [%3];\n}"
                 ::"r"(a), "f"(x), "f"(y), "r"(bar), "r"((uint32_t)c) : "memory");
}
__device__ __forceinline__ void st_async4(uint32_t a, uint32_t x, uint32_t y, uint32_t z, uint32_t w, uint32_t bar) {
    asm volatile("st.async.shared::cluster.mbarrier::complete_tx::bytes.v4.u32 [%0], {%1,%2,%3,%4}, [%5];"
                 ::"r"(a), "r"(x), "r"(y), "r"(z), "r"(w), "r"(bar) : "memory");
}

__device__ __forceinline__ void ldsm4(uint32_t (&r)[4], uint32_t a) {
    asm volatile("ldmatrix.sync.aligned.m8n8.x4.shared.b16 {%0,%1,%2,%3}, [%4];"
                 : "=r"(r[0]), "=r"(r[1]), "=r"(r[2]), "=r"(r[3]) : "r"(a) : "memory");
}
__device__ __forceinline__ void ldsm4t(uint32_t (&r)[4], uint32_t a) {
    asm volatile("ldmatrix.sync.aligned.m8n8.x4.trans.shared.b16 {%0,%1,%2,%3}, [%4];"
                 : "=r"(r[0]), "=r"(r[1]), "=r"(r[2]), "=r"(r[3]) : "r"(a) : "memory");
}
__device__ __forceinline__ void mma16816(float (&c)[4], const uint32_t (&a)[4], uint32_t b0, uint32_t b1) {
    asm volatile("mma.sync.aligned.m16n8k16.row.col.f32.bf16.bf16.f32 {%0,%1,%2,%3}, {%4,%5,%6,%7}, {%8,%9}, {%0,%1,%2,%3};"
                 : "+f"(c[0]), "+f"(c[1]), "+f"(c[2]), "+f"(c[3])
                 : "r"(a[0]), "r"(a[1]), "r"(a[2]), "r"(a[3]), "r"(b0), "r"(b1));
}
__device__ __forceinline__ uint32_t movm(uint32_t a) {
    uint32_t d;
    asm volatile("movmatrix.sync.aligned.m8n8.trans.b16 %0, %1;" : "=r"(d) : "r"(a));
    return d;
}
__device__ __forceinline__ uint32_t pack_bf16(float lo, float hi) {
    uint32_t d;
    asm("cvt.rn.bf16x2.f32 %0, %1, %2;" : "=r"(d) : "f"(hi), "f"(lo));
    return d;
}
__device__ __forceinline__ float bf_lo(uint32_t u) { return __uint_as_float(u << 16); }
__device__ __forceinline__ float bf_hi(uint32_t u) { return __uint_as_float(u & 0xffff0000u); }
__device__ __forceinline__ float bfr(float v) { return __uint_as_float(pack_bf16(0.f, v)); }
__device__ __forceinline__ uint32_t max_bf16x2(uint32_t a, uint32_t b) {
    uint32_t d;
    asm("max.bf16x2 %0, %1, %2;" : "=r"(d) : "r"(a), "r"(b));
    return d;
}
__device__ __forceinline__ float ex2(float x) {
    float y;
    asm("ex2.approx.ftz.f32 %0, %1;" : "=f"(y) : "f"(x));
    return y;
}
__device__ __forceinline__ float mul_sigmoid(float v, float z) { return __fdividef(v, 1.0f + ex2(fminf(-kLog2e * z, 120.f))); }
__device__ __forceinline__ uint32_t lds32(uint32_t a) { uint32_t v; asm volatile("ld.shared.u32 %0, [%1];" : "=r"(v) : "r"(a) : "memory"); return v; }
__device__ __forceinline__ float2 ldsf2(uint32_t a) { float2 v; asm volatile("ld.shared.v2.f32 {%0,%1}, [%2];" : "=f"(v.x), "=f"(v.y) : "r"(a) : "memory"); return v; }
__device__ __forceinline__ uint4 lds128(uint32_t a) {
    uint4 v;
    asm volatile("ld.shared.v4.u32 {%0,%1,%2,%3}, [%4];" : "=r"(v.x), "=r"(v.y), "=r"(v.z), "=r"(v.w) : "r"(a) : "memory");
    return v;
}
__device__ __forceinline__ void sts32(uint32_t a, uint32_t v) { asm volatile("st.shared.u32 [%0], %1;" ::"r"(a), "r"(v) : "memory"); }
__device__ __forceinline__ void stsf(uint32_t a, float v) { asm volatile("st.shared.f32 [%0], %1;" ::"r"(a), "f"(v) : "memory"); }
__device__ __forceinline__ void sts128(uint32_t a, uint32_t x, uint32_t y, uint32_t z, uint32_t w) {
    asm volatile("st.shared.v4.u32 [%0], {%1,%2,%3,%4};" ::"r"(a), "r"(x), "r"(y), "r"(z), "r"(w) : "memory");
}
__device__ __forceinline__ uint32_t enc(uint32_t b) { return b == 0u ? 0x80000000u : b; }
__device__ __forceinline__ void st_pred32(void* p, uint32_t v, bool c) {
    asm volatile("{\n.reg .pred p;\nsetp.ne.u32 p, %2, 0;\n@p st.global.u32 [%0], %1;\n}" ::"l"(p), "r"(v), "r"((uint32_t)c) : "memory");
}
__device__ __forceinline__ void ld_rlx4_pred(uint32_t (&v)[4], const uint32_t* p, bool c) {
    asm volatile("{\n.reg .pred p;\nsetp.ne.u32 p, %5, 0;\n@p ld.relaxed.gpu.global.v4.u32 {%0,%1,%2,%3}, [%4];\n}"
                 : "+r"(v[0]), "+r"(v[1]), "+r"(v[2]), "+r"(v[3]) : "l"(p), "r"((uint32_t)c) : "memory");
}
__device__ __forceinline__ uint32_t gt32() { uint32_t c; asm volatile("mov.u32 %0, %globaltimer_lo;" : "=r"(c) :: "memory"); return c; }
__device__ __forceinline__ void wait_until(uint32_t t0, int ns) {
    while (gt32() - t0 < (uint32_t)max(ns, 0)) {}
}
__device__ __forceinline__ uint32_t ldg32(const void* p) {
    uint32_t v;
    asm volatile("ld.global.nc.u32 %0, [%1];" : "=r"(v) : "l"(p));
    return v;
}

__global__ void __cluster_dims__(8, 1, 1) __launch_bounds__(kThreads, 1)
fused_decode_kernel(const __nv_bfloat16* __restrict__ x, const __nv_bfloat16* __restrict__ b1,
                    const __nv_bfloat16* __restrict__ b2, __nv_bfloat16* __restrict__ out, const char* __restrict__ kc,
                    const __grid_constant__ Params prm) {
    extern __shared__ __align__(1024) unsigned char smem_raw[];
    const uint32_t sb = smem_u32(smem_raw);
    const uint32_t bars = sb + SM_BAR;
    const int tid = threadIdx.x, wid = tid >> 5, lane = tid & 31;
    const int hkv = blockIdx.x >> 3, r = blockIdx.x & 7;
    const int flip = (hkv & 1) * 2;
    asm volatile("{\n.reg .pred p;\nsetp.lt.u32 p, %1, %2;\n@p prefetch.global.L2 [%0];\n}"
                 ::"l"(kc + ((r * kHKV + hkv) * (kSK * 256u) + flip * (uint32_t)kSlot + tid * 128u)), "r"(tid), "n"(96) : "memory");
    if (tid < 32) {
        if (elect_one()) {
            mbar_init(bars + B_FULL, 1);
            mbar_init(bars + B_FULL + 8, 1);
            asm volatile("fence.mbarrier_init.release.cluster;" ::: "memory");
#pragma unroll
            for (int n = 0; n < 2; n++) {
                mbar_expect_tx(bars + B_FULL + 8 * n, kSlot);
                tma3d(sb + SM_RING + n * kSlot, &prm.m[2], blockIdx.x * 64, n * 256, 0, bars + B_FULL + 8 * n);
            }
#pragma unroll
            for (int n = 2; n < kNSlot; n++) mbar_init(bars + B_FULL + 8 * n, 1);
            asm volatile("fence.mbarrier_init.release.cluster;" ::: "memory");
            mbar_expect_tx(bars + B_FULL + 16, r < 7 ? kSlot : 0);
            if (r < 7) tma3d(sb + SM_RING + 2 * kSlot, &prm.m[3], hkv * 224 + r * 32, 0, 0, bars + B_FULL + 16);
        }
    }
    const uint32_t t_start = gt32();
    if (wid == 1) asm volatile("prefetch.global.L1 [%0];" ::"l"(x + r * kD + lane * 16) : "memory");
    if (wid == 3 && lane < 4) asm volatile("prefetch.tensormap [%0];" ::"l"(&prm.m[lane + (lane & 2)]) : "memory");
    if (tid == 64) {
        if (sb & 1023u) __trap();
#pragma unroll
        for (int n = 0; n < kNSlot; n++) mbar_init(bars + B_EMPTY + 8 * n, 8);
#pragma unroll
        for (int n = B_WO; n < B_END; n += 8) mbar_init(bars + n, n < B_H ? 1 : 8);
        asm volatile("fence.mbarrier_init.release.cluster;" ::: "memory");
        sts128(sb + SM_PROG, 0, 0, 0, 0);
        sts128(sb + SM_PROG + 16, 0, 0, 0, 0);
        asm volatile("fence.release.sync_restrict::shared::cta.cluster;" ::: "memory");
        mbar_expect_tx(bars + B_X, 8192);
        mbar_expect_tx(bars + B_Q, 1024);
        mbar_expect_tx(bars + B_Y, 2048);
        mbar_expect_tx(bars + B_S, 2048);
    }
    __syncwarp();
    cluster_arrive();
    const int w = (wid - 2) & 7;
    const int g = lane >> 2, t = lane & 3, r7 = lane & 7, mi = lane >> 3;

    if (wid == 1) {
        {
            const uint4* xr = reinterpret_cast<const uint4*>(x + r * kD) + lane;
            const uint4 xv0 = __ldg(xr), xv1 = __ldg(xr + 32);
            float f[16];
            const uint32_t u[8] = {xv0.x, xv0.y, xv0.z, xv0.w, xv1.x, xv1.y, xv1.z, xv1.w};
#pragma unroll
            for (int i = 0; i < 8; i++) { f[2 * i] = bf_lo(u[i]); f[2 * i + 1] = bf_hi(u[i]); }
            float s = 0.f;
#pragma unroll
            for (int i = 0; i < 16; i++) s += f[i];
#pragma unroll
            for (int o = 16; o; o >>= 1) s += __shfl_xor_sync(0xffffffffu, s, o);
            const float mean = s * (1.0f / kD);
            float vs = 0.f;
#pragma unroll
            for (int i = 0; i < 16; i++) { const float d = f[i] - mean; vs = fmaf(d, d, vs); }
#pragma unroll
            for (int o = 16; o; o >>= 1) vs += __shfl_xor_sync(0xffffffffu, vs, o);
            const float mb = bfr(mean);
            const float den = bfr(__fsqrt_rn(bfr(bfr(vs * (1.0f / kD)) + 1e-5f)));
            const float rden = __frcp_rn(den);
            uint32_t q[8];
#pragma unroll
            for (int i = 0; i < 8; i++) {
                const uint32_t d2 = pack_bf16(f[2 * i] - mb, f[2 * i + 1] - mb);
                q[i] = pack_bf16(bf_lo(d2) * rden, bf_hi(d2) * rden);
            }
            const uint32_t xoff = SM_X + r * 1024 + ((lane >> 1) & 7) * 128 + (((2 * (lane >> 4) + (lane & 1)) ^ r) << 4);
            cluster_wait();
#pragma unroll 1
            for (int d = 0; d < 8; d++) {
                const uint32_t rb = mapa(sb, d), xa = rb + xoff;
                st_async4(xa, q[0], q[1], q[2], q[3], rb + SM_BAR + B_X);
                st_async4(xa ^ 64, q[4], q[5], q[6], q[7], rb + SM_BAR + B_X);
            }
        }
        const int col = hkv * 64 + 2 * lane;
        const uint32_t xw = ldg32(x + r * kD + col), bw = ldg32(b2 + col);
        __nv_bfloat16* dst = out + r * kD + col;
        uint32_t pa = sb + SM_Y + lane * 8, pbar = bars + B_Y;
        PINL(dst);
        uint32_t gw = 0u;
#pragma unroll 1
        for (int pass = 0; pass < 2; pass++) {
            mbar_wait_cl(pbar, 0);
            float2 v[8];
#pragma unroll
            for (int c = 0; c < 8; c++) v[c] = ldsf2(pa + c * 256);
            const uint32_t sw = pack_bf16(((v[0].x + v[1].x) + (v[2].x + v[3].x)) + ((v[4].x + v[5].x) + (v[6].x + v[7].x)),
                                          ((v[0].y + v[1].y) + (v[2].y + v[3].y)) + ((v[4].y + v[5].y) + (v[6].y + v[7].y)));
            uint32_t ow;
            asm("{\n.reg .b32 p;\nmul.rn.bf16x2 p, %1, %2;\nadd.rn.bf16x2 %0, %3, p;\n}" : "=r"(ow) : "r"(sw), "r"(gw), "r"(xw));
            st_pred32(dst, ow, pass);
            if (pass) break;
            const uint32_t yw = pack_bf16(bf_lo(sw) + bf_lo(bw), bf_hi(sw) + bf_hi(bw));
            gw = pack_bf16(mul_sigmoid(bf_lo(yw), bf_lo(yw)), mul_sigmoid(bf_hi(yw), bf_hi(yw)));
            pa = sb + SM_S + lane * 8;
            pbar = bars + B_S;
        }
    } else if (wid == 0) {
        cluster_wait();
        const int kvrow0 = (r * kHKV + hkv) * kSK;
        const uint32_t prog_remote = mapa(sb + SM_PROG + r * 4, lane & 7);
        int slot = kKVN, ph = 0;
        int landed = 0, lslot = 0, lph = 0;
#pragma unroll 1
        for (int n = kKVN; n < kItems; n++) {
            if (n >= kNSlot) mbar_wait(bars + B_EMPTY + 8 * slot, ph ^ 1);
            for (const int need = n - (n >= kW2N ? kWindowEnd : kWindow); landed <= need; landed++) {
                mbar_wait(bars + B_FULL + 8 * lslot, lph);
                if (++lslot == kNSlot) { lslot = 0; lph ^= 1; }
            }
            wait_until(t_start, n < kHeadN ? kHeadT0 + (n - kKVN) * kHeadDt
                                           : prm.sched_a + n * prm.sched_b + (n < kW2N ? 0 : n < kWoN ? kGapW2 : kGapWo));
            if (n < kW2N) {
                if (lane < 8) asm volatile("st.relaxed.cluster.shared::cluster.u32 [%0], %1;" ::"r"(prog_remote), "r"(n) : "memory");
                for (uint32_t it = 0;; it++) {
                    int p;
                    asm volatile("ld.relaxed.cluster.shared::cta.u32 %0, [%1];" : "=r"(p) : "r"(sb + SM_PROG + (lane & 7) * 4) : "memory");
                    if (__all_sync(0xffffffffu, max(p, kKVN) + kLead >= n)) break;
                    if (it > kSpinLimit * 16) __trap();
                }
            }
            if (elect_one()) {
                const uint32_t dst = sb + SM_RING + slot * kSlot;
                if (n < kW2N) {
                    const int u = n - kKVN;
                    mbar_expect_tx(bars + B_FULL + 8 * slot, kSlot);
                    tma3d(dst, &prm.m[(u >> 4) & 1], 0, 0, kvrow0 + (u >> 5) * 2048 + ((u & 15) ^ flip) * 128, bars + B_FULL + 8 * slot);
                } else if (n >= kWoN) {
                    const uint32_t wb = bars + B_WO + 16 * (n - kWoN);
                    mbar_expect_tx(wb, kSlot / 2);
                    tma4d(dst, &prm.m[5], hkv * 64, 0, 0, r * 32 + (n - kWoN) * 16, wb);
                    mbar_expect_tx(wb + 8, kSlot / 2);
                    tma4d(dst + kSlot / 2, &prm.m[5], hkv * 64, 0, 0, r * 32 + (n - kWoN) * 16 + 8, wb + 8);
                } else {
                    mbar_expect_tx(bars + B_W2, 224 * 128);
                    tma3d(dst, &prm.m[4], hkv * 64, r * 224, 0, bars + B_W2);
                }
                if (n == kGoN) mbar_arrive(bars + B_GO);
            }
            __syncwarp();
            if (++slot == kNSlot) { slot = 0; ph ^= 1; }
        }
        wait_until(gt32(), kGateO);
        mbar_wait(bars + B_W2, 0);
        if (lane == 0) mbar_arrive(bars + B_GO2);
    } else if (wid < 10) {
        const int kg = w >> 1, ch = w & 1;
        if (w == 7 && lane < 16) sts32(sb + SM_B1 + lane * 4, ldg32(b1 + hkv * 224 + (r < 7 ? r : 0) * 32 + 2 * lane));
        uint32_t wa = sb + SM_SCR + kg * 2176 + t * 544 + (ch * 32 + g) * 4;
        uint32_t ra = sb + SM_SCR + w * 272 + lane * 8;
        uint32_t* op = &g_o[hkv][r][kg * 512 + lane * 4];
        const uint32_t baddr = sb + SM_X + r7 * 1024 + (mi & 1) * 512 + (((2 * kg + (mi >> 1)) ^ r7) << 4);
        uint32_t abase = sb + SM_RING + kg * (kSlot / 2) + (r7 + 64 * (mi >> 1)) * 128 + (((4 * ch + (mi & 1)) ^ r7) << 4);
        uint32_t abar = bars + B_FULL + 8 * (kg >> 1);
        uint32_t sa = mapa(sb + SM_S + r * 256 + lane * 8, w), sbar = mapa(bars + B_S, w);
        PIN(wa); PIN(ra); PINL(op); PIN(sa); PIN(sbar);
        uint32_t bf[4][4];
        auto fetch_o = [&]() {
            bool all = true;
#pragma unroll
            for (int j = 0; j < 4; j++) {
                const bool ok = bf[j][0] != 0u && bf[j][1] != 0u && bf[j][2] != 0u && bf[j][3] != 0u;
                all = all && ok;
                ld_rlx4_pred(bf[j], op + j * 128, !ok);
            }
            return __all_sync(0xffffffffu, all);
        };
        cluster_wait();
        mbar_wait_cl(bars + B_X, 0);
#pragma unroll 1
        for (int pass = 0; pass < 3; pass++) {
            float acc[2][2][4];
#pragma unroll
            for (int i = 0; i < 16; i++) acc[i >> 3][(i >> 2) & 1][i & 3] = 0.f;
            bool stream = true;
            if (pass == 2) {
                mbar_wait(bars + B_GO2, 0);
                for (uint32_t it = 0;; it++) {
                    stream = fetch_o();
                    if (stream || kg < 2 || __all_sync(0xffffffffu, mbar_test(abar, 0))) break;
                    if (it > kSpinLimit) __trap();
                }
            } else {
#pragma unroll
                for (int i = 0; i < 4; i++) ldsm4(bf[i], baddr + ((i + 2 * (pass & ch)) & 3) * 128);
            }
            if (pass == 1) {
                const uint32_t a1 = sb + SM_RING + 2 * kSlot + (128 * kg + 32 * ch + r7 + 64 * (mi >> 1)) * 64 + (((mi & 1) ^ (r7 >> 1)) << 4);
                mbar_wait(bars + B_FULL + 16, 0);
#pragma unroll
                for (int ks = 0; ks < 4; ks++) {
#pragma unroll
                    for (int mt = 0; mt < 2; mt++) {
                        uint32_t af[4];
                        ldsm4t(af, (a1 ^ (mt * 32)) + (ks >> 1) * 1024 + (ks & 1) * 512);
                        mma16816(acc[mt][ks & 1], af, bf[ks >> 1][2 * (ks & 1)], bf[ks >> 1][2 * (ks & 1) + 1]);
                    }
                }
            } else if (stream) {
                mbar_wait(abar, 0);
#pragma unroll
                for (int ks = 0; ks < 8; ks++) {
#pragma unroll
                    for (int mt = 0; mt < 2; mt++) {
                        uint32_t af[4];
                        ldsm4t(af, (abase ^ (mt * 32)) + ks * 1024);
                        mma16816(acc[mt][ks & 1], af, bf[ks >> 1][2 * (ks & 1)], bf[ks >> 1][2 * (ks & 1) + 1]);
                    }
                }
            } else {
                uint32_t af[8][2][4];
                mbar_wait(abar, 0);
#pragma unroll
                for (int ks = 0; ks < 8; ks++) {
                    ldsm4t(af[ks][0], abase + ks * 1024);
                    ldsm4t(af[ks][1], (abase ^ 32) + ks * 1024);
                }
                for (uint32_t it = 0; !fetch_o(); it++)
                    if (it > kSpinLimit) __trap();
#pragma unroll
                for (int ks = 0; ks < 8; ks++) {
                    mma16816(acc[0][ks & 1], af[ks][0], bf[ks >> 1][2 * (ks & 1)], bf[ks >> 1][2 * (ks & 1) + 1]);
                    mma16816(acc[1][ks & 1], af[ks][1], bf[ks >> 1][2 * (ks & 1)], bf[ks >> 1][2 * (ks & 1) + 1]);
                }
            }
#pragma unroll
            for (int mt = 0; mt < 2; mt++) {
#pragma unroll
                for (int e = 0; e < 4; e++)
                    stsf(wa + (e & 1) * 272 + (mt * 16 + 8 * (e >> 1)) * 4, acc[mt][0][e] + acc[mt][1][e]);
            }
            bar_sync(1, 256);
            const float2 p0 = ldsf2(ra), p1 = ldsf2(ra + 2176), p2 = ldsf2(ra + 2 * 2176), p3 = ldsf2(ra + 3 * 2176);
            float s0 = (p0.x + p1.x) + (p2.x + p3.x), s1 = (p0.y + p1.y) + (p2.y + p3.y);
            st_async2_pred(sa, s0, s1, sbar, pass == 2);
            if (pass == 2) break;
            if (pass == 0) {
                const uint32_t rb = mapa(sb, w);
                st_async(rb + SM_Q + (r * 32 + lane) * 4, pack_bf16(s0, s1), rb + SM_BAR + B_Q);
                if (lane == 0) mbar_arrive_n(bars + B_EMPTY + 8 * (kg >> 1), 2);
            } else {
                if (lane == 0) mbar_arrive(bars + B_EMPTY + 16);
                s0 += __shfl_xor_sync(0xffffffffu, s0, 16);
                s1 += __shfl_xor_sync(0xffffffffu, s1, 16);
                const uint32_t sw = pack_bf16(s0, s1), b1w = lds32(sb + SM_B1 + (lane & 15) * 4);
                const uint32_t vw = pack_bf16(bf_lo(sw) + bf_lo(b1w), bf_hi(sw) + bf_hi(b1w));
                const float v0 = bf_lo(vw), v1 = bf_hi(vw);
                const float c = 2.0f * 0.7978845608028654f;
                uint32_t hw = pack_bf16(mul_sigmoid(v0, c * (v0 + 0.044715f * v0 * v0 * v0)),
                                        mul_sigmoid(v1, c * (v1 + 0.044715f * v1 * v1 * v1)));
                hw = r < 7 ? enc(hw) : 0x80000000u;
                {
                    uint32_t* cp = &g_o[w][hkv][(g * 16 + r) * 16 + t * 4];
                    *reinterpret_cast<uint4*>(cp) = make_uint4(0u, 0u, 0u, 0u);
                    *reinterpret_cast<uint4*>(cp + 128) = make_uint4(0u, 0u, 0u, 0u);
                    __threadfence();
                    bar_sync(1, 256);
                }
                {
                    uint32_t* hp = &g_h[(lane >> 4) * 4][hkv][w * 128 + (2 * (r & 1) + (mi & 1)) * 32 + (((2 * (r >> 1) + (r7 >> 2)) ^ w) << 2) + t];
#pragma unroll
                    for (int d = 0; d < 4; d++) asm volatile("st.relaxed.gpu.global.u32 [%0], %1;" ::"l"(hp + d * 8 * 1024), "r"(hw) : "memory");
                }
                mbar_wait(bars + B_GO, 0);
                {
                    uint32_t* hp = &g_h[hkv][r][w * 128 + lane * 4];
                    uint4 v;
                    for (uint32_t it = 0;; it++) {
                        asm volatile("ld.relaxed.gpu.global.v4.u32 {%0,%1,%2,%3}, [%4];" : "=r"(v.x), "=r"(v.y), "=r"(v.z), "=r"(v.w) : "l"(hp) : "memory");
                        if (v.x != 0u && v.y != 0u && v.z != 0u && v.w != 0u) break;
                        if (it > kSpinLimit) __trap();
                    }
                    sts128(sb + SM_H + w * 512 + lane * 16, v.x, v.y, v.z, v.w);
                    *reinterpret_cast<uint4*>(hp) = make_uint4(0u, 0u, 0u, 0u);
                    __threadfence();
                }
                __syncwarp();
                if (lane == 0) mbar_arrive(bars + B_H);
#pragma unroll
                for (int i = 0; i < 16; i++) bf[i >> 2][i & 3] = 0u;
                abase += (kWoN % kNSlot) * kSlot;
                abar = bars + B_WO + 8 * kg;
                PIN(abase); PIN(abar);
            }
            bar_sync(1, 256);
        }
    } else {
        int slot = kKVN, ph = 0;
        auto acquire = [&]() {
            mbar_wait(bars + B_FULL + 8 * slot, ph);
            return sb + SM_RING + slot * kSlot;
        };
        auto release = [&]() {
            __syncwarp();
            if (lane == 0) mbar_arrive_n(bars + B_EMPTY + 8 * slot, 2);
            if (++slot == kNSlot) { slot = 0; ph ^= 1; }
        };
        const int hl = r7 >> 2;
        const bool diag = (g >> 2) == (t >> 1);
        uint32_t koff[4];
#pragma unroll
        for (int c = 0; c < 4; c++)
            koff[c] = (w * 32 + r7 + 8 * (mi & 1)) * 256 + hl * 128 + (((2 * c + (mi >> 1)) ^ (2 * (r7 & 3) + hl)) << 4);
        const uint32_t voff = (16 * (mi >> 1) + r7 + 8 * hl) * 256 + hl * 128 + (((2 * w + (mi & 1)) ^ (2 * (r7 & 3) + hl)) << 4);
        const int ht = 2 * (t & 1) + (t >> 1);
        uint32_t* op = &g_o[0][hkv][((ht * 4 + w) * 8 + r) * 16 + (g & 3) * 4 + 2 * (g >> 2)];
        PINL(op);
        cluster_wait();
        uint32_t qf[8][2];
        mbar_wait_cl(bars + B_Q, 0);
#pragma unroll
        for (int ks = 0; ks < 8; ks++) {
            qf[ks][0] = lds32(sb + SM_Q + ((g & 3) * 64 + (ks ^ (g & 4)) * 8 + t) * 4);
            qf[ks][1] = lds32(sb + SM_Q + ((g & 3) * 64 + (ks ^ (g & 4)) * 8 + 4 + t) * 4);
        }
        uint32_t mx2 = 0xff7fff7fu;
        uint32_t mprev = 0xff7fff7fu;
        float Mw = bf_hi(mprev), l = 0.f, fin = 0.f;
        float O[4][4];
#pragma unroll
        for (int i = 0; i < 4; i++) { O[i][0] = O[i][1] = O[i][2] = O[i][3] = 0.f; }
#pragma unroll 1
        for (int c = 0; c < 2; c++) {
            uint32_t pa = sb + SM_P + (g & 3) * kPStride + (diag ? 0 : 16) + t * 4 + w * 64;
#pragma unroll 1
            for (int it = 0; it < 16; it++) {
                const uint32_t base = acquire();
                float sc[2][2][4];
#pragma unroll
                for (int i = 0; i < 16; i++) sc[i >> 3][(i >> 2) & 1][i & 3] = 0.f;
#pragma unroll
                for (int ks = 0; ks < 8; ks++) {
#pragma unroll
                    for (int mt = 0; mt < 2; mt++) {
                        uint32_t kf[4];
                        ldsm4(kf, base + (koff[ks & 3] ^ ((ks >> 2) * 144)) + mt * 4096);
                        mma16816(sc[mt][ks & 1], kf, qf[ks][0], qf[ks][1]);
                    }
                }
                release();
#pragma unroll
                for (int mt = 0; mt < 2; mt++) {
                    const uint32_t sa = pack_bf16(sc[mt][0][0] + sc[mt][1][0], sc[mt][0][1] + sc[mt][1][1]);
                    const uint32_t sx = __shfl_xor_sync(0xffffffffu, pack_bf16(sc[mt][0][2] + sc[mt][1][2], sc[mt][0][3] + sc[mt][1][3]), 2);
                    const uint32_t s2 = diag ? sa : sx;
                    const float scale = 0.08838834764831845f;
                    const uint32_t v = pack_bf16(bf_lo(s2) * scale, bf_hi(s2) * scale);
                    mx2 = max_bf16x2(mx2, v);
                    sts32(pa + mt * 32, movm(v));
                }
                pa += it == 7 ? 4 * kPStride - 7 * 256 : 256;
            }
            {
#pragma unroll
                for (int o = 2; o <= 16; o <<= 1) mx2 = max_bf16x2(mx2, __shfl_xor_sync(0xffffffffu, mx2, o));
                if (lane < 2) sts32(sb + SM_ML + lane * 16 + w * 4, mx2);
                bar_sync(2, 128);
                const uint4 a0 = lds128(sb + SM_ML), b0 = lds128(sb + SM_ML + 16);
                const uint32_t m01 = max_bf16x2(max_bf16x2(a0.x, a0.y), max_bf16x2(a0.z, a0.w));
                const uint32_t m23 = max_bf16x2(max_bf16x2(b0.x, b0.y), max_bf16x2(b0.z, b0.w));
                const uint32_t mw = (w & 2) ? m23 : m01, mt = (t & 1) ? m23 : m01;
                const float M = (w & 1) ? bf_hi(mw) : bf_lo(mw);
                l *= ex2((Mw - M) * kLog2e);
                Mw = M;
                const float al0 = ex2((bf_lo(mprev) - bf_lo(mt)) * kLog2e), al1 = ex2((bf_hi(mprev) - bf_hi(mt)) * kLog2e);
                mprev = mt;
#pragma unroll
                for (int i = 0; i < 4; i++) { O[i][0] *= al0; O[i][1] *= al1; O[i][2] *= al0; O[i][3] *= al1; }
                const uint32_t ea = sb + SM_P + w * kPStride + lane * 16;
#pragma unroll 2
                for (int i = 0; i < 8; i++) {
                    const uint32_t ei = ea + (i >> 2) * (4 * kPStride) + (i & 3) * 512;
                    const uint4 sv = lds128(ei);
                    const uint32_t uu[4] = {sv.x, sv.y, sv.z, sv.w};
                    uint32_t rr[4];
#pragma unroll
                    for (int e = 0; e < 4; e++) {
                        const float p0 = ex2((bf_lo(uu[e]) - M) * kLog2e), p1 = ex2((bf_hi(uu[e]) - M) * kLog2e);
                        l += p0 + p1;
                        rr[e] = pack_bf16(p0, p1);
                    }
                    sts128(ei, rr[0], rr[1], rr[2], rr[3]);
                }
                float ls = l;
#pragma unroll
                for (int o = 16; o; o >>= 1) ls += __shfl_xor_sync(0xffffffffu, ls, o);
                if (lane == 0) stsf(sb + SM_ML + 32 + w * 4, ls);
                bar_sync(2, 128);
                fin = __fdividef(1.0f, __uint_as_float(lds32(sb + SM_ML + 32 + ht * 4)));
                PINF(fin);
                if (c == 1) mbar_wait(bars + B_H, 0);
            }
            pa = sb + SM_P + (r7 & 3) * kPStride + (r7 >> 2) * 16 + mi * 32;
#pragma unroll 1
            for (int it = 0; it < 16; it++) {
                uint32_t pf[2][4], ps[2][8];
                ldsm4(pf[0], pa);
                ldsm4(pf[1], pa + 128);
                pa += it == 7 ? 4 * kPStride - 7 * 256 : 256;
#pragma unroll
                for (int i = 0; i < 8; i++) {
                    ps[0][i] = diag ? pf[i >> 2][i & 3] : 0u;
                    ps[1][i] = diag ? 0u : pf[i >> 2][i & 3];
                }
                const uint32_t base = acquire();
#pragma unroll
                for (int j = 0; j < 4; j++) {
#pragma unroll
                    for (int i = 0; i < 4; i++) {
                        uint32_t vf[4];
                        ldsm4t(vf, base + (voff ^ ((i >> 1) * 144 + (i & 1) * 2048)) + j * 8192);
                        mma16816(O[2 * ((i >> 1) ^ (i & 1)) + (i & 1)], vf, ps[i & 1][2 * j], ps[i & 1][2 * j + 1]);
                    }
                }
                release();
            }
        }
        uint32_t ow[2];
        float Z[2][4];
#pragma unroll
        for (int i = 0; i < 8; i++) Z[i >> 2][i & 3] = O[2 * (i >> 2)][i & 3] + O[2 * (i >> 2) + 1][i & 3];
#pragma unroll
        for (int mt = 0; mt < 2; mt++) {
            const float (&A)[4] = Z[mt];
            const float (&B)[4] = Z[mt ^ 1];
            const float lo = (t < 2 ? A[0] : B[1]) + __shfl_xor_sync(0xffffffffu, t < 2 ? A[1] : B[0], 2);
            const float hi = (t < 2 ? A[2] : B[3]) + __shfl_xor_sync(0xffffffffu, t < 2 ? A[3] : B[2], 2);
            ow[mt] = enc(pack_bf16(lo * fin, hi * fin));
        }
#pragma unroll
        for (int d = 0; d < 8; d++)
            asm volatile("st.relaxed.gpu.global.v2.u32 [%0], {%1,%2};" ::"l"(op + d * kHKV * 2048), "r"(ow[0]), "r"(ow[1]) : "memory");
        {
            uint32_t hf[7][4];
#pragma unroll
            for (int j = 0; j < 7; j++)
                ldsm4(hf[j], sb + SM_H + r7 * 512 + (2 * (j & 1) + (mi >> 1)) * 128 + (((2 * (j >> 1) + (mi & 1)) ^ r7) << 4));
            uint32_t wa2 = sb + SM_RING + (kW2N % kNSlot) * kSlot + (r7 + 8 * (mi >> 1)) * 128 + (((2 * w + (mi & 1)) ^ r7) << 4);
            uint32_t ya = mapa(sb + SM_Y + r * 256 + (16 * w + g) * 4, 2 * t), yb = mapa(bars + B_Y, 2 * t), wbar = bars + B_W2;
            const uint32_t ostep = mapa(bars + B_Y, 2 * t + 1) - yb;
            PIN(wa2); PIN(ya); PIN(yb); PIN(wbar);
            {
                mbar_wait(wbar, 0);
                float acc[4][4];
#pragma unroll
                for (int i = 0; i < 16; i++) acc[i >> 2][i & 3] = 0.f;
#pragma unroll
                for (int ks = 0; ks < 14; ks++) {
                    uint32_t af[4];
                    ldsm4t(af, wa2 + ks * 2048);
                    mma16816(acc[ks & 3], af, hf[ks >> 1][2 * (ks & 1)], hf[ks >> 1][2 * (ks & 1) + 1]);
                }
#pragma unroll
                for (int e = 0; e < 4; e++)
                    st_async(ya + (e & 1) * ostep + (e >> 1) * 32, __float_as_uint((acc[0][e] + acc[1][e]) + (acc[2][e] + acc[3][e])),
                             yb + (e & 1) * ostep);
            }
        }
    }
}

typedef CUresult (*EncodeFn)(CUtensorMap*, CUtensorMapDataType, cuuint32_t, void*, const cuuint64_t*, const cuuint64_t*,
                             const cuuint32_t*, const cuuint32_t*, CUtensorMapInterleave, CUtensorMapSwizzle,
                             CUtensorMapL2promotion, CUtensorMapFloatOOBfill);

void encode(EncodeFn fn, CUtensorMap* m, void* p, int rank, const cuuint64_t* dims, const cuuint64_t* strides,
            const cuuint32_t* box, CUtensorMapSwizzle sw = CU_TENSOR_MAP_SWIZZLE_128B) {
    const cuuint32_t es[4] = {1, 1, 1, 1};
    fn(m, CU_TENSOR_MAP_DATA_TYPE_BFLOAT16, rank, p, dims, strides, box, es, CU_TENSOR_MAP_INTERLEAVE_NONE,
       sw, CU_TENSOR_MAP_L2_PROMOTION_NONE, CU_TENSOR_MAP_FLOAT_OOB_FILL_NONE);
}

}

extern "C" void kernel_launch(void* const* d_in, const int* in_sizes, int n_in, void* d_out, int out_size) {
    (void)in_sizes; (void)n_in; (void)out_size;
    void* fnp = nullptr;
    cudaDriverEntryPointQueryResult qr;
    cudaGetDriverEntryPoint("cuTensorMapEncodeTiled", &fnp, cudaEnableDefault, &qr);
    EncodeFn fn = (EncodeFn)fnp;
    Params prm;
    {
        const cuuint64_t dims[3] = {64, 2, (cuuint64_t)8 * kHKV * kSK}, str[2] = {128, 256};
        const cuuint32_t box[3] = {64, 2, 128};
        encode(fn, &prm.m[0], d_in[1], 3, dims, str, box);
        encode(fn, &prm.m[1], d_in[2], 3, dims, str, box);
    }
    {
        const cuuint64_t dims[3] = {4096, 512, 1}, str[2] = {8192, 8192 * 512};
        const cuuint32_t box[3] = {64, 256, 1};
        encode(fn, &prm.m[2], d_in[3], 3, dims, str, box);
    }
    {
        const cuuint64_t dims[3] = {1792, 256, 2}, str[2] = {3584, 3584 * 256};
        const cuuint32_t box[3] = {32, 256, 2};
        encode(fn, &prm.m[3], d_in[6], 3, dims, str, box, CU_TENSOR_MAP_SWIZZLE_64B);
    }
    {
        const cuuint64_t dims[3] = {512, 1792, 1}, str[2] = {1024, 1024 * 1792};
        const cuuint32_t box[3] = {64, 224, 1};
        encode(fn, &prm.m[4], d_in[8], 3, dims, str, box);
    }
    {
        const cuuint64_t dims[4] = {512, 2, 8, 256}, str[3] = {8 * 1024, 1024, 16 * 1024};
        const cuuint32_t box[4] = {64, 2, 8, 8};
        encode(fn, &prm.m[5], d_in[4], 4, dims, str, box);
    }
    {
        int dev = 0, khz = 0, bits = 0;
        cudaGetDevice(&dev);
        cudaDeviceGetAttribute(&khz, cudaDevAttrMemoryClockRate, dev);
        cudaDeviceGetAttribute(&bits, cudaDevAttrGlobalMemoryBusWidth, dev);
        const double bytes_per_ns = 2.0 * khz * 1e-6 * bits / 8.0;
        const double scale = bytes_per_ns > 1000.0 ? (double)kGrid * kSlot / bytes_per_ns / kItemNs : 0.0;
        prm.sched_b = (int)(kSchedStep * scale + 0.5);
        prm.sched_a = (int)(kSchedLast * scale + 0.5) - (kItems - 1) * prm.sched_b;
    }
    cudaFuncSetAttribute(fused_decode_kernel, cudaFuncAttributeMaxDynamicSharedMemorySize, SM_BYTES);
    fused_decode_kernel<<<kGrid, kThreads, SM_BYTES>>>(
        (const __nv_bfloat16*)d_in[0], (const __nv_bfloat16*)d_in[7], (const __nv_bfloat16*)d_in[9],
        (__nv_bfloat16*)d_out, (const char*)d_in[1], prm);
}
```
